```python
import torch

def _softmax(x, axis=-1):
    return torch.softmax(x, dim=axis)

def _gelu(x):
    return torch.nn.functional.gelu(x, approximate='tanh')

def _silu(x):
    return torch.nn.functional.silu(x)

def _sigmoid(x):
    return torch.sigmoid(x)

def _layernorm(x, axis=-1, eps=1e-05):
    m = x.mean(dim=axis, keepdim=True)
    v = x.var(dim=axis, keepdim=True, unbiased=False)
    return (x - m) / torch.sqrt(v + eps)

def _scatter_add(tgt, idx, src, axis=0):
    return tgt.clone().index_add_(axis, idx, src)

def _segment_sum(src, seg, n):
    out = torch.zeros((n,) + src.shape[1:], dtype=src.dtype)
    return out.index_add_(0, seg, src)

def _pad(x, pw):
    flat = tuple((v for pair in reversed(pw) for v in pair))
    return torch.nn.functional.pad(x, flat)
kernel_name = 'adaLN_cond__mha_block__glu_gated_swiglu__prompt'

def setup_inputs():

    _w = lambda a: (lambda t: t.to(torch.bfloat16) if t.is_floating_point() else t)(torch.as_tensor(a))

    def _A_setup():
        B, S, D, H = (1, 2048, 512, 32)
        return {'x': _w((lambda *s: torch.randn(*s, dtype=torch.bfloat16) * 0.05)(B, S, D)), 'wqkv': _w((lambda *s: torch.randn(*s, dtype=torch.bfloat16) * 0.05)(D, 3 * D)), 'wo': _w((lambda *s: torch.randn(*s, dtype=torch.bfloat16) * 0.05)(D, D))}
    _A_in = _A_setup()

    def _B_setup():
        B, S, D, F = (1, 2048, 512, 1376)
        return {'x': _w((lambda *s: torch.randn(*s, dtype=torch.bfloat16) * 0.05)(B, S, D)), 'w1': _w((lambda *s: torch.randn(*s, dtype=torch.bfloat16) * 0.8)(D, F) * (2.0 / D) ** 0.5), 'w3': _w((lambda *s: torch.randn(*s, dtype=torch.bfloat16) * 0.8)(D, F) * (2.0 / D) ** 0.5), 'w2': _w((lambda *s: torch.randn(*s, dtype=torch.bfloat16) * 0.8)(F, D) * (2.0 / F) ** 0.5)}
    _B_in = _B_setup()
    return {'A_x': _A_in['x'], 'A_wqkv': _A_in['wqkv'], 'A_wo': _A_in['wo'], 'B_x': _B_in['x'], 'B_w1': _B_in['w1'], 'B_w3': _B_in['w3'], 'B_w2': _B_in['w2'], 'c': _w((lambda *s: torch.randn(*s, dtype=torch.bfloat16) * 0.2)(1, 512) * 8.0), 'w_mod': _w((lambda *s: torch.randn(*s, dtype=torch.bfloat16) * 0.2)(512, 6 * 512) * 512 ** (-0.5) * 8.0)}

def reference(A_x, A_wqkv, A_wo, B_x, B_w1, B_w3, B_w2, c, w_mod):

    def _A_ref(x, wqkv, wo):
        B, S, D = x.shape
        H = 32
        Dh = D // H
        qkv = (lambda x, *d: x.permute(*d))((x @ wqkv).reshape(B, S, 3, H, Dh), 2, 0, 3, 1, 4)
        q, k, v = (qkv[0], qkv[1], qkv[2])
        scores = torch.einsum('bhqd,bhkd->bhqk', q, k) * Dh ** (-0.5)
        p = _softmax(scores, axis=-1)
        o = torch.einsum('bhqk,bhkd->bhqd', p, v)
        return (lambda x, *d: x.permute(*d))(o, 0, 2, 1, 3).reshape(B, S, D) @ wo

    def _B_ref(x, w1, w3, w2):
        gate = torch.einsum('bsd,df->bsf', x, w1)
        up = torch.einsum('bsd,df->bsf', x, w3)
        h = _silu(gate) * up
        out = torch.einsum('bsf,fd->bsd', h, w2)
        return out
    x = A_x
    mod = (_silu(c) @ w_mod).reshape(c.shape[0], 6, 1, -1)
    sa, ca, ga, sb, cb, gb = (mod[:, 0].clone(), mod[:, 1].clone(), mod[:, 2].clone(), mod[:, 3].clone(), mod[:, 4].clone(), mod[:, 5].clone())
    h = _layernorm(x, axis=-1) * (1 + ca) + sa
    x = x + ga * _A_ref(h, A_wqkv, A_wo)
    h = _layernorm(x, axis=-1) * (1 + cb) + sb
    x = x + gb * _B_ref(h, B_w1, B_w3, B_w2)
    return x
```

```cpp
#include <cuda_runtime.h>
#include <cuda_bf16.h>
#include <cuda_fp16.h>
#include <cuda.h>
#include <stdint.h>

typedef __nv_bfloat16 bf16;
constexpr int S_ = 2048, D_ = 512, F_ = 1376, NH = 32;
constexpr int KS_F = F_ / 16;

__device__ __align__(16) bf16 g_mod[6 * D_];
__device__ uint4 g_q[NH * 128 * 32];
__device__ uint4 g_k[NH * 2 * S_];
__device__ uint4 g_v[NH * 2 * S_];
__device__ uint4 g_attn[128 * 32 * 32];
__device__ uint4 g_x1[128 * 32 * 32];
__device__ uint4 g_act[128 * KS_F * 32];
__device__ unsigned g_flags[2 * 128 * 8];

__device__ __forceinline__ uint32_t smem_u32(const void* p) { return (uint32_t)__cvta_generic_to_shared(p); }
__device__ __forceinline__ void mbar_init(uint32_t b, uint32_t n) { asm volatile("mbarrier.init.shared::cta.b64 [%0], %1;" ::"r"(b), "r"(n) : "memory"); }
__device__ __forceinline__ void mbar_expect(uint32_t b, uint32_t bytes) { asm volatile("mbarrier.arrive.expect_tx.shared::cta.b64 _, [%0], %1;" ::"r"(b), "r"(bytes) : "memory"); }
__device__ __forceinline__ void mbar_arrive(uint32_t b) { asm volatile("mbarrier.arrive.shared::cta.b64 _, [%0];" ::"r"(b) : "memory"); }
__device__ __forceinline__ void mbar_wait(uint32_t b, uint32_t ph) {
  asm volatile("{.reg .pred p; .reg .u32 n; mov.u32 n, 0;\n"
               "W: mbarrier.try_wait.parity.shared::cta.b64 p, [%0], %1;\n"
               "@p bra D; add.u32 n, n, 1; setp.lt.u32 p, n, 0x4000000; @p bra W; trap;\n"
               "D: }" ::"r"(b), "r"(ph) : "memory");
}
__device__ __forceinline__ void mbar_wait_cluster(uint32_t b, uint32_t ph) {
  asm volatile("{.reg .pred p; .reg .u32 n; mov.u32 n, 0;\n"
               "W: mbarrier.try_wait.parity.acquire.cluster.shared::cta.b64 p, [%0], %1;\n"
               "@p bra D; add.u32 n, n, 1; setp.lt.u32 p, n, 0x4000000; @p bra W; trap;\n"
               "D: }" ::"r"(b), "r"(ph) : "memory");
}
__device__ __forceinline__ void tma2d(uint32_t dst, const CUtensorMap* m, int c0, int c1, uint32_t bar) {
  asm volatile("cp.async.bulk.tensor.2d.shared::cluster.global.mbarrier::complete_tx::bytes [%0], [%1, {%3, %4}], [%2];"
               ::"r"(dst), "l"(m), "r"(bar), "r"(c0), "r"(c1) : "memory");
}
__device__ __forceinline__ void tma5d(uint32_t dst, const CUtensorMap* m, int c0, int c4, uint32_t bar) {
  asm volatile("cp.async.bulk.tensor.5d.shared::cluster.global.mbarrier::complete_tx::bytes [%0], [%1, {%3, 0, 0, 0, %4}], [%2];"
               ::"r"(dst), "l"(m), "r"(bar), "r"(c0), "r"(c4) : "memory");
}
__device__ __forceinline__ void bulk_g2s(uint32_t dst, const void* src, uint32_t bytes, uint32_t bar) {
  asm volatile("cp.async.bulk.shared::cluster.global.mbarrier::complete_tx::bytes [%0], [%1], %2, [%3];"
               ::"r"(dst), "l"(src), "r"(bytes), "r"(bar) : "memory");
}
__device__ __forceinline__ void l2_prefetch(const void* src, uint32_t bytes) {
  asm volatile("cp.async.bulk.prefetch.L2.global [%0], %1;" ::"l"(src), "r"(bytes) : "memory");
}
__device__ __forceinline__ void pdl_wait() { asm volatile("griddepcontrol.wait;" ::: "memory"); }
__device__ __forceinline__ void pdl_trigger() { asm volatile("griddepcontrol.launch_dependents;" ::: "memory"); }
__device__ __forceinline__ void wg_fence() { asm volatile("wgmma.fence.sync.aligned;" ::: "memory"); }
__device__ __forceinline__ void wg_commit() { asm volatile("wgmma.commit_group.sync.aligned;" ::: "memory"); }
template <int N> __device__ __forceinline__ void wg_wait() { asm volatile("wgmma.wait_group.sync.aligned %0;" ::"n"(N) : "memory"); }
template <int N> __device__ __forceinline__ void reg_fence(float* r) {
#pragma unroll
  for (int i = 0; i < N; i++) asm volatile("" : "+f"(r[i])::"memory");
}
template <int N> __device__ __forceinline__ void reg_fence(uint32_t* r) {
#pragma unroll
  for (int i = 0; i < N; i++) asm volatile("" : "+r"(r[i])::"memory");
}
__device__ __forceinline__ uint4 ldg128(const void* p) {
  uint4 v; asm volatile("ld.global.L1::no_allocate.v4.u32 {%0,%1,%2,%3}, [%4];" : "=r"(v.x), "=r"(v.y), "=r"(v.z), "=r"(v.w) : "l"(p) : "memory"); return v;
}
__device__ __forceinline__ uint4 ldg128_nc(const void* p) {
  uint4 v; asm volatile("ld.global.nc.L1::no_allocate.v4.u32 {%0,%1,%2,%3}, [%4];" : "=r"(v.x), "=r"(v.y), "=r"(v.z), "=r"(v.w) : "l"(p)); return v;
}
__device__ __forceinline__ uint32_t pack_bf16(float lo, float hi) { uint32_t r; asm("cvt.rn.bf16x2.f32 %0, %1, %2;" : "=r"(r) : "f"(hi), "f"(lo)); return r; }
__device__ __forceinline__ uint32_t pack_f16(float lo, float hi) { uint32_t r; asm("cvt.rn.satfinite.f16x2.f32 %0, %1, %2;" : "=r"(r) : "f"(hi), "f"(lo)); return r; }
__device__ __forceinline__ float bf_lo(uint32_t v) { return __uint_as_float(v << 16); }
__device__ __forceinline__ float bf_hi(uint32_t v) { return __uint_as_float(v & 0xffff0000u); }
__device__ __forceinline__ uint32_t bf_fma2(uint32_t a, uint32_t b, uint32_t c) { uint32_t r; asm("fma.rn.bf16x2 %0, %1, %2, %3;" : "=r"(r) : "r"(a), "r"(b), "r"(c)); return r; }
__device__ __forceinline__ float ex2f(float x) { float r; asm("ex2.approx.ftz.f32 %0, %1;" : "=f"(r) : "f"(x)); return r; }
__device__ __forceinline__ float rcpf(float x) { float r; asm("rcp.approx.ftz.f32 %0, %1;" : "=f"(r) : "f"(x)); return r; }
__device__ __forceinline__ uint32_t desc_lo(uint32_t addr, uint32_t lbo) { return ((addr & 0x3FFFF) >> 4) | ((lbo >> 4) << 16); }
#define MMA(fn, off, accum, d, a, dlo) fn(d, a, dlo, off, accum)
__device__ __forceinline__ uint64_t desc_plain(uint32_t addr, uint32_t lbo, uint32_t sbo) {
  return (uint64_t)((addr & 0x3FFFF) >> 4) | ((uint64_t)(lbo >> 4) << 16) | ((uint64_t)(sbo >> 4) << 32);
}
__device__ __forceinline__ void mma_n64(float* d, const uint32_t* a, uint32_t dlo, int off, int acc) {
  asm volatile("{.reg .pred p; .reg .b32 t; .reg .b64 ds; add.u32 t, %36, %37; mov.b64 ds, {t, 0x40000040}; setp.ne.b32 p, %38, 0;\n"
    "wgmma.mma_async.sync.aligned.m64n64k16.f32.bf16.bf16 {%0,%1,%2,%3,%4,%5,%6,%7,%8,%9,%10,%11,%12,%13,%14,%15,%16,%17,%18,%19,%20,%21,%22,%23,%24,%25,%26,%27,%28,%29,%30,%31}, "
    "{%32,%33,%34,%35}, ds, p, 1, 1, 1;}"
    : "+f"(d[0]),"+f"(d[1]),"+f"(d[2]),"+f"(d[3]),"+f"(d[4]),"+f"(d[5]),"+f"(d[6]),"+f"(d[7]),"+f"(d[8]),"+f"(d[9]),"+f"(d[10]),"+f"(d[11]),"+f"(d[12]),"+f"(d[13]),"+f"(d[14]),"+f"(d[15]),"+f"(d[16]),"+f"(d[17]),"+f"(d[18]),"+f"(d[19]),"+f"(d[20]),"+f"(d[21]),"+f"(d[22]),"+f"(d[23]),"+f"(d[24]),"+f"(d[25]),"+f"(d[26]),"+f"(d[27]),"+f"(d[28]),"+f"(d[29]),"+f"(d[30]),"+f"(d[31])
    : "r"(a[0]), "r"(a[1]), "r"(a[2]), "r"(a[3]), "r"(dlo), "r"(off >> 4), "r"(acc));
}
__device__ __forceinline__ void mma_n128(float* d, const uint32_t* a, uint32_t dlo, int off, int acc) {
  asm volatile("{.reg .pred p; .reg .b32 t; .reg .b64 ds; add.u32 t, %68, %69; mov.b64 ds, {t, 0x40000040}; setp.ne.b32 p, %70, 0;\n"
    "wgmma.mma_async.sync.aligned.m64n128k16.f32.bf16.bf16 {%0,%1,%2,%3,%4,%5,%6,%7,%8,%9,%10,%11,%12,%13,%14,%15,%16,%17,%18,%19,%20,%21,%22,%23,%24,%25,%26,%27,%28,%29,%30,%31,%32,%33,%34,%35,%36,%37,%38,%39,%40,%41,%42,%43,%44,%45,%46,%47,%48,%49,%50,%51,%52,%53,%54,%55,%56,%57,%58,%59,%60,%61,%62,%63}, "
    "{%64,%65,%66,%67}, ds, p, 1, 1, 1;}"
    : "+f"(d[0]),"+f"(d[1]),"+f"(d[2]),"+f"(d[3]),"+f"(d[4]),"+f"(d[5]),"+f"(d[6]),"+f"(d[7]),"+f"(d[8]),"+f"(d[9]),"+f"(d[10]),"+f"(d[11]),"+f"(d[12]),"+f"(d[13]),"+f"(d[14]),"+f"(d[15]),"+f"(d[16]),"+f"(d[17]),"+f"(d[18]),"+f"(d[19]),"+f"(d[20]),"+f"(d[21]),"+f"(d[22]),"+f"(d[23]),"+f"(d[24]),"+f"(d[25]),"+f"(d[26]),"+f"(d[27]),"+f"(d[28]),"+f"(d[29]),"+f"(d[30]),"+f"(d[31]),"+f"(d[32]),"+f"(d[33]),"+f"(d[34]),"+f"(d[35]),"+f"(d[36]),"+f"(d[37]),"+f"(d[38]),"+f"(d[39]),"+f"(d[40]),"+f"(d[41]),"+f"(d[42]),"+f"(d[43]),"+f"(d[44]),"+f"(d[45]),"+f"(d[46]),"+f"(d[47]),"+f"(d[48]),"+f"(d[49]),"+f"(d[50]),"+f"(d[51]),"+f"(d[52]),"+f"(d[53]),"+f"(d[54]),"+f"(d[55]),"+f"(d[56]),"+f"(d[57]),"+f"(d[58]),"+f"(d[59]),"+f"(d[60]),"+f"(d[61]),"+f"(d[62]),"+f"(d[63])
    : "r"(a[0]), "r"(a[1]), "r"(a[2]), "r"(a[3]), "r"(dlo), "r"(off >> 4), "r"(acc));
}
__device__ __forceinline__ void mma_n48(float* d, const uint32_t* a, uint32_t dlo, int off, int acc) {
  asm volatile("{.reg .pred p; .reg .b32 t; .reg .b64 ds; add.u32 t, %28, %29; mov.b64 ds, {t, 0x40000040}; setp.ne.b32 p, %30, 0;\n"
    "wgmma.mma_async.sync.aligned.m64n48k16.f32.bf16.bf16 {%0,%1,%2,%3,%4,%5,%6,%7,%8,%9,%10,%11,%12,%13,%14,%15,%16,%17,%18,%19,%20,%21,%22,%23}, "
    "{%24,%25,%26,%27}, ds, p, 1, 1, 1;}"
    : "+f"(d[0]),"+f"(d[1]),"+f"(d[2]),"+f"(d[3]),"+f"(d[4]),"+f"(d[5]),"+f"(d[6]),"+f"(d[7]),"+f"(d[8]),"+f"(d[9]),"+f"(d[10]),"+f"(d[11]),"+f"(d[12]),"+f"(d[13]),"+f"(d[14]),"+f"(d[15]),"+f"(d[16]),"+f"(d[17]),"+f"(d[18]),"+f"(d[19]),"+f"(d[20]),"+f"(d[21]),"+f"(d[22]),"+f"(d[23])
    : "r"(a[0]), "r"(a[1]), "r"(a[2]), "r"(a[3]), "r"(dlo), "r"(off >> 4), "r"(acc));
}
__device__ __forceinline__ void mma_pv24(float* d, const uint32_t* a, uint32_t dlo, int off, int acc) {
  asm volatile("{.reg .pred p; .reg .b32 t; .reg .b64 ds; add.u32 t, %16, %17; mov.b64 ds, {t, 0x800}; setp.ne.b32 p, %18, 0;\n"
    "wgmma.mma_async.sync.aligned.m64n24k16.f32.f16.f16 {%0,%1,%2,%3,%4,%5,%6,%7,%8,%9,%10,%11}, "
    "{%12,%13,%14,%15}, ds, p, 1, 1, 1;}"
    : "+f"(d[0]),"+f"(d[1]),"+f"(d[2]),"+f"(d[3]),"+f"(d[4]),"+f"(d[5]),"+f"(d[6]),"+f"(d[7]),"+f"(d[8]),"+f"(d[9]),"+f"(d[10]),"+f"(d[11])
    : "r"(a[0]), "r"(a[1]), "r"(a[2]), "r"(a[3]), "r"(dlo), "r"(off >> 4), "r"(acc));
}
__device__ __forceinline__ void mma_qk256(uint32_t* d, const uint32_t* a, uint64_t desc) {
  asm volatile("wgmma.mma_async.sync.aligned.m64n256k16.f16.f16.f16 {%0,%1,%2,%3,%4,%5,%6,%7,%8,%9,%10,%11,%12,%13,%14,%15,%16,%17,%18,%19,%20,%21,%22,%23,%24,%25,%26,%27,%28,%29,%30,%31,%32,%33,%34,%35,%36,%37,%38,%39,%40,%41,%42,%43,%44,%45,%46,%47,%48,%49,%50,%51,%52,%53,%54,%55,%56,%57,%58,%59,%60,%61,%62,%63}, "
    "{%64,%65,%66,%67}, %68, 0, 1, 1, 0;"
    : "=r"(d[0]),"=r"(d[1]),"=r"(d[2]),"=r"(d[3]),"=r"(d[4]),"=r"(d[5]),"=r"(d[6]),"=r"(d[7]),"=r"(d[8]),"=r"(d[9]),"=r"(d[10]),"=r"(d[11]),"=r"(d[12]),"=r"(d[13]),"=r"(d[14]),"=r"(d[15]),"=r"(d[16]),"=r"(d[17]),"=r"(d[18]),"=r"(d[19]),"=r"(d[20]),"=r"(d[21]),"=r"(d[22]),"=r"(d[23]),"=r"(d[24]),"=r"(d[25]),"=r"(d[26]),"=r"(d[27]),"=r"(d[28]),"=r"(d[29]),"=r"(d[30]),"=r"(d[31]),"=r"(d[32]),"=r"(d[33]),"=r"(d[34]),"=r"(d[35]),"=r"(d[36]),"=r"(d[37]),"=r"(d[38]),"=r"(d[39]),"=r"(d[40]),"=r"(d[41]),"=r"(d[42]),"=r"(d[43]),"=r"(d[44]),"=r"(d[45]),"=r"(d[46]),"=r"(d[47]),"=r"(d[48]),"=r"(d[49]),"=r"(d[50]),"=r"(d[51]),"=r"(d[52]),"=r"(d[53]),"=r"(d[54]),"=r"(d[55]),"=r"(d[56]),"=r"(d[57]),"=r"(d[58]),"=r"(d[59]),"=r"(d[60]),"=r"(d[61]),"=r"(d[62]),"=r"(d[63])
    : "r"(a[0]), "r"(a[1]), "r"(a[2]), "r"(a[3]), "l"(desc));
}
__device__ __forceinline__ void mma_qk128(uint32_t* d, const uint32_t* a, uint64_t desc) {
  asm volatile("wgmma.mma_async.sync.aligned.m64n128k16.f16.f16.f16 {%0,%1,%2,%3,%4,%5,%6,%7,%8,%9,%10,%11,%12,%13,%14,%15,%16,%17,%18,%19,%20,%21,%22,%23,%24,%25,%26,%27,%28,%29,%30,%31}, "
    "{%32,%33,%34,%35}, %36, 0, 1, 1, 0;"
    : "=r"(d[0]),"=r"(d[1]),"=r"(d[2]),"=r"(d[3]),"=r"(d[4]),"=r"(d[5]),"=r"(d[6]),"=r"(d[7]),"=r"(d[8]),"=r"(d[9]),"=r"(d[10]),"=r"(d[11]),"=r"(d[12]),"=r"(d[13]),"=r"(d[14]),"=r"(d[15]),"=r"(d[16]),"=r"(d[17]),"=r"(d[18]),"=r"(d[19]),"=r"(d[20]),"=r"(d[21]),"=r"(d[22]),"=r"(d[23]),"=r"(d[24]),"=r"(d[25]),"=r"(d[26]),"=r"(d[27]),"=r"(d[28]),"=r"(d[29]),"=r"(d[30]),"=r"(d[31])
    : "r"(a[0]), "r"(a[1]), "r"(a[2]), "r"(a[3]), "l"(desc));
}

__global__ void __launch_bounds__(256) k_mod(const bf16* __restrict__ c, const bf16* __restrict__ wm) {
  pdl_trigger();
  __shared__ float red[8][32];
  const int tid = threadIdx.x, r = tid >> 2, cc = tid & 3, lane = tid & 31, w = tid >> 5;
  uint4 v[8];
#pragma unroll
  for (int i = 0; i < 8; i++) v[i] = ldg128_nc(wm + (size_t)(r + 64 * i) * (6 * D_) + blockIdx.x * 32 + cc * 8);
  if (blockIdx.x < 8) g_flags[blockIdx.x * 256 + tid] = 0;
  float acc[8];
#pragma unroll
  for (int e = 0; e < 8; e++) acc[e] = 0.f;
#pragma unroll
  for (int i = 0; i < 8; i++) {
    float cv = __bfloat162float(c[r + 64 * i]);
    float s = __bfloat162float(__float2bfloat16(cv / (1.f + __expf(-cv))));
    uint32_t u[4] = {v[i].x, v[i].y, v[i].z, v[i].w};
#pragma unroll
    for (int e = 0; e < 4; e++) { acc[2 * e] += s * bf_lo(u[e]); acc[2 * e + 1] += s * bf_hi(u[e]); }
  }
#pragma unroll
  for (int e = 0; e < 8; e++) {
    acc[e] += __shfl_xor_sync(~0u, acc[e], 4);
    acc[e] += __shfl_xor_sync(~0u, acc[e], 8);
    acc[e] += __shfl_xor_sync(~0u, acc[e], 16);
  }
  if (lane < 4) {
#pragma unroll
    for (int e = 0; e < 8; e++) red[w][lane * 8 + e] = acc[e];
  }
  __syncthreads();
  if (tid < 32) {
    float s = 0.f;
#pragma unroll
    for (int i = 0; i < 8; i++) s += red[i][tid];
    const int col = blockIdx.x * 32 + tid, seg = col >> 9;
    bf16 m = __float2bfloat16(s);
    if (seg == 1 || seg == 4) m = __float2bfloat16(1.f + __bfloat162float(m));
    g_mod[col] = m;
  }
}

constexpr int QKV_SMEM = 24 * 8192 + 2048 + 256 + 1024;
__global__ void __launch_bounds__(256, 1) k_qkv(const __grid_constant__ CUtensorMap tm_w, const bf16* __restrict__ x) {
  extern __shared__ __align__(1024) uint8_t sp[];
  const uint32_t sb = smem_u32(sp), dlo = desc_lo(sb, 8192);
  if (sb & 1023) __trap();
  const uint32_t bars = sb + 24 * 8192 + 2048;
  const int tid = threadIdx.x, lane = tid & 31, w = tid >> 5, g = lane >> 2, q = lane & 3;
  const int nt = blockIdx.x & 7, rb16 = (blockIdx.x >> 3) * 8 + w;
  pdl_trigger();
  if (tid == 0) {
    for (int i = 0; i < 6; i++) mbar_init(bars + 8 * i, 1);
    asm volatile("fence.mbarrier_init.release.cluster;" ::: "memory");
    for (int i = 0; i < 6; i++) {
      mbar_expect(bars + 8 * i, 4 * 8192);
      for (int kb = 0; kb < 4; kb++)
        tma5d(sb + (i * 4 + kb) * 8192, &tm_w, nt * 192 + (i >> 1) * 64, ((i & 1) * 4 + kb) * 2, bars + 8 * i);
    }
  }
  uint32_t a[128];
  {
    const bf16* x0 = x + (size_t)(rb16 * 16 + g) * D_ + q * 8;
#pragma unroll
    for (int b = 0; b < 16; b++) {
      uint4 u = ldg128_nc(x0 + b * 32), v = ldg128_nc(x0 + 8 * D_ + b * 32);
      a[8 * b] = u.x; a[8 * b + 2] = u.y; a[8 * b + 4] = u.z; a[8 * b + 6] = u.w;
      a[8 * b + 1] = v.x; a[8 * b + 3] = v.y; a[8 * b + 5] = v.z; a[8 * b + 7] = v.w;
    }
    float s[4] = {0.f, 0.f, 0.f, 0.f};
#pragma unroll
    for (int i = 0; i < 128; i++) { s[i & 1] += bf_lo(a[i]); s[2 + (i & 1)] += bf_hi(a[i]); }
    float m0 = s[0] + s[2], m1 = s[1] + s[3];
    m0 += __shfl_xor_sync(~0u, m0, 1); m1 += __shfl_xor_sync(~0u, m1, 1);
    m0 += __shfl_xor_sync(~0u, m0, 2); m1 += __shfl_xor_sync(~0u, m1, 2);
    m0 *= -1.f / D_; m1 *= -1.f / D_;
    const uint32_t one = 0x3F803F80u, nm0 = pack_bf16(m0, m0), nm1 = pack_bf16(m1, m1);
    s[0] = s[1] = s[2] = s[3] = 0.f;
#pragma unroll
    for (int i = 0; i < 128; i++) {
      a[i] = bf_fma2(a[i], one, (i & 1) ? nm1 : nm0);
      float lo = bf_lo(a[i]), hi = bf_hi(a[i]);
      s[i & 1] += lo * lo; s[2 + (i & 1)] += hi * hi;
    }
    float v0 = s[0] + s[2], v1 = s[1] + s[3];
    v0 += __shfl_xor_sync(~0u, v0, 1); v1 += __shfl_xor_sync(~0u, v1, 1);
    v0 += __shfl_xor_sync(~0u, v0, 2); v1 += __shfl_xor_sync(~0u, v1, 2);
    v0 = rsqrtf(v0 * (1.f / D_) + 1e-5f); v1 = rsqrtf(v1 * (1.f / D_) + 1e-5f);
    const uint32_t r0 = pack_bf16(v0, v0), r1 = pack_bf16(v1, v1);
#pragma unroll
    for (int i = 0; i < 128; i++) a[i] = bf_fma2(a[i], (i & 1) ? r1 : r0, 0x80008000u);
  }
  pdl_wait();
  if (tid < 128) *(uint4*)(sp + 24 * 8192 + tid * 16) = ldg128((const uint8_t*)g_mod + tid * 16);
  __syncthreads();
  float acc[2][32];
#pragma unroll
  for (int kb = 0; kb < 8; kb++) {
#pragma unroll
    for (int b = 2 * kb; b < 2 * kb + 2; b++) {
      uint4 sa = *(const uint4*)(sp + 24 * 8192 + b * 64 + q * 16), ca = *(const uint4*)(sp + 24 * 8192 + 1024 + b * 64 + q * 16);
      uint32_t su[4] = {sa.x, sa.y, sa.z, sa.w}, cu[4] = {ca.x, ca.y, ca.z, ca.w};
#pragma unroll
      for (int j = 0; j < 8; j++) a[8 * b + j] = bf_fma2(a[8 * b + j], cu[j >> 1], su[j >> 1]);
    }
    if ((kb & 3) == 0) mbar_wait(bars + 8 * (kb >> 2), 0);
    wg_fence();
#pragma unroll
    for (int ks = 0; ks < 4; ks++) MMA(mma_n64, kb * 8192 + ks * 2048, kb | ks, acc[0], a + (kb * 4 + ks) * 4, dlo);
  }
  wg_commit();
#pragma unroll
  for (int p = 0; p < 3; p++) {
    if (p < 2) {
      mbar_wait(bars + 8 * (2 * p + 2), 0);
      mbar_wait(bars + 8 * (2 * p + 3), 0);
      wg_fence();
#pragma unroll
      for (int ks = 0; ks < 32; ks++) MMA(mma_n64, (p + 1) * 65536 + ks * 2048, ks, acc[(p + 1) & 1], a + ks * 4, dlo);
      wg_commit();
      wg_wait<1>();
    } else {
      wg_wait<0>();
    }
    float* d = acc[p & 1];
    reg_fence<32>(d);
    const int col = nt * 192 + p * 64, sec = col >> 9, h0 = (col & 511) >> 4;
    if (sec == 0) {
      const float sc = 0.25f * 1.4426950408889634f;
#pragma unroll
      for (int hh = 0; hh < 4; hh++)
        g_q[((h0 + hh) * 128 + rb16) * 32 + lane] =
            make_uint4(pack_f16(d[8 * hh] * sc, d[8 * hh + 1] * sc), pack_f16(d[8 * hh + 2] * sc, d[8 * hh + 3] * sc),
                       pack_f16(d[8 * hh + 4] * sc, d[8 * hh + 5] * sc), pack_f16(d[8 * hh + 6] * sc, d[8 * hh + 7] * sc));
    } else {
      uint32_t* dst = (uint32_t*)(sec == 1 ? g_k : g_v) + (size_t)(h0 * 2 * S_ + rb16 * 16) * 4 + lane;
#pragma unroll
      for (int jj = 0; jj < 8; jj++) {
        dst[jj * S_ * 4] = pack_f16(d[4 * jj], d[4 * jj + 1]);
        dst[jj * S_ * 4 + 32] = pack_f16(d[4 * jj + 2], d[4 * jj + 3]);
      }
    }
  }
}

__device__ __forceinline__ uint32_t h_max(uint32_t a, uint32_t b) { uint32_t r; asm("max.f16x2 %0, %1, %2;" : "=r"(r) : "r"(a), "r"(b)); return r; }
__device__ __forceinline__ uint32_t h_add(uint32_t a, uint32_t b) { uint32_t r; asm("add.rn.f16x2 %0, %1, %2;" : "=r"(r) : "r"(a), "r"(b)); return r; }
__device__ __forceinline__ uint32_t h_sub(uint32_t a, uint32_t b) { uint32_t r; asm("sub.rn.f16x2 %0, %1, %2;" : "=r"(r) : "r"(a), "r"(b)); return r; }
__device__ __forceinline__ uint32_t h_mul(uint32_t a, uint32_t b) { uint32_t r; asm("mul.rn.f16x2 %0, %1, %2;" : "=r"(r) : "r"(a), "r"(b)); return r; }
__device__ __forceinline__ uint32_t h_fma(uint32_t a, uint32_t b, uint32_t c) { uint32_t r; asm("fma.rn.f16x2 %0, %1, %2, %3;" : "=r"(r) : "r"(a), "r"(b), "r"(c)); return r; }
__device__ __forceinline__ uint32_t h_fma_relu(uint32_t a, uint32_t b, uint32_t c) { uint32_t r; asm("fma.rn.relu.f16x2 %0, %1, %2, %3;" : "=r"(r) : "r"(a), "r"(b), "r"(c)); return r; }
__device__ __forceinline__ uint32_t h_ex2(uint32_t a) { uint32_t r; asm("ex2.approx.f16x2 %0, %1;" : "=r"(r) : "r"(a)); return r; }
__device__ __forceinline__ float h_lo(uint32_t v) { return __half2float(__ushort_as_half((unsigned short)(v & 0xffff))); }
__device__ __forceinline__ float h_hi(uint32_t v) { return __half2float(__ushort_as_half((unsigned short)(v >> 16))); }

__device__ __forceinline__ uint32_t exp2_fma(uint32_t s, uint32_t cp) {
  const uint32_t u = h_fma_relu(s, 0x18001800u, cp);
  const uint32_t n = h_mul(u, 0x02000200u);
  const uint32_t f = h_fma(n, 0xF800F800u, u);
  uint32_t p = h_fma(f, 0x630D630Du, 0x47C047C0u);
  p = h_fma(p, f, 0x298C298Cu);
  p = h_fma(p, f, 0x08000800u);
  return p + (n << 10);
}

#define NPOLY 8
__device__ __forceinline__ constexpr bool is_poly(int i) { return ((i & 15) * NPOLY) / 16 != (((i & 15) + 1) * NPOLY) / 16; }

constexpr int ATT_SMEM = 5 * 32768 + 128 + 1024;
__global__ void __launch_bounds__(512, 1) k_attn(const bf16* __restrict__ wo, const bf16* __restrict__ w1,
                                                 const bf16* __restrict__ w3, const bf16* __restrict__ w2) {
  extern __shared__ __align__(1024) uint8_t sp[];
  const uint32_t sb = smem_u32(sp);
  if (sb & 1023) __trap();
  const uint32_t bars = sb + 5 * 32768;
  const int tid = threadIdx.x, lane = tid & 31, w = tid >> 5;
  const int head = blockIdx.x >> 2, quarter = blockIdx.x & 3;
  if (tid == 0) {
    for (int i = 0; i < 8; i++) mbar_init(bars + 8 * i, 1);
    asm volatile("fence.mbarrier_init.release.cluster;" ::: "memory");
  }
#pragma unroll
  for (int i = 0; i < 4; i++) *(uint4*)(sp + 4 * 32768 + (i * 512 + tid) * 16) = make_uint4(0x3C003C00u, 0x3C003C00u, 0x3C003C00u, 0x3C003C00u);
  asm volatile("fence.proxy.async.shared::cta;" ::: "memory");
  __syncthreads();
  pdl_wait();
  if (tid == 0) {
    for (int i = 0; i < 8; i++) {
      mbar_expect(bars + 8 * i, 16384);
      bulk_g2s(sb + i * 4096, g_k + (head * 2) * S_ + i * 256, 4096, bars + 8 * i);
      bulk_g2s(sb + 32768 + i * 4096, g_k + (head * 2 + 1) * S_ + i * 256, 4096, bars + 8 * i);
      bulk_g2s(sb + 65536 + i * 4096, g_v + (head * 2) * S_ + i * 256, 4096, bars + 8 * i);
      bulk_g2s(sb + 98304 + i * 4096, g_v + (head * 2 + 1) * S_ + i * 256, 4096, bars + 8 * i);
    }
  }
  pdl_trigger();
  if (tid == 64) {
    l2_prefetch((const uint8_t*)wo + blockIdx.x * 4096, 4096);
    l2_prefetch((const uint8_t*)w1 + blockIdx.x * 11008, 11008);
    l2_prefetch((const uint8_t*)w3 + blockIdx.x * 11008, 11008);
    l2_prefetch((const uint8_t*)w2 + blockIdx.x * 11008, 11008);
  }
  const uint64_t dk0 = desc_plain(sb, 32768, 128);
  const uint32_t dv0 = desc_lo(sb + 65536, 128);
#pragma unroll 1
  for (int t = 0; t < 2; t++) {
    const int rb16 = quarter * 32 + (w >> 2) * 8 + t * 4 + (w & 3);
    uint32_t qf[4];
    { uint4 u = ldg128(g_q + (head * 128 + rb16) * 32 + lane); qf[0] = u.x; qf[1] = u.y; qf[2] = u.z; qf[3] = u.w; }
    float o[12];
#pragma unroll
    for (int i = 0; i < 12; i++) o[i] = 0.f;
    uint32_t M = 0xFBFFFBFFu, cprev = 0x7BFF7BFFu;
    uint32_t s[64];
#pragma unroll 1
    for (int kb = 0; kb < 8; kb++) {
      if (t == 0) mbar_wait(bars + 8 * kb, 0);
      wg_fence();
      mma_qk256(s, qf, dk0 + kb * 256);
      wg_commit();
      wg_wait<0>();
      reg_fence<64>(s);
      uint32_t m0 = h_max(s[0], s[2]), m1 = h_max(s[1], s[3]), m2 = h_max(s[4], s[6]), m3 = h_max(s[5], s[7]);
#pragma unroll
      for (int i = 8; i < 64; i += 8) {
        m0 = h_max(h_max(m0, s[i]), s[i + 2]); m1 = h_max(h_max(m1, s[i + 1]), s[i + 3]);
        m2 = h_max(h_max(m2, s[i + 4]), s[i + 6]); m3 = h_max(h_max(m3, s[i + 5]), s[i + 7]);
      }
      m0 = h_max(m0, m2); m1 = h_max(m1, m3);
      M = h_max(h_max(__byte_perm(m0, m1, 0x5410), __byte_perm(m0, m1, 0x7632)), M);
      M = h_max(M, __shfl_xor_sync(~0u, M, 1));
      M = h_max(M, __shfl_xor_sync(~0u, M, 2));
      const uint32_t c = h_sub(h_sub(0x660E660Eu, M), 0x66006600u);
      const uint32_t cp = h_fma(c, 0x18001800u, 0x26802680u);
      const uint32_t dl = h_sub(c, cprev);
      cprev = c;
      const float a0 = ex2f(h_lo(dl)), a1 = ex2f(h_hi(dl));
      const uint32_t c0 = __byte_perm(c, c, 0x1010), c1 = __byte_perm(c, c, 0x3232);
      const uint32_t p0 = __byte_perm(cp, cp, 0x1010), p1 = __byte_perm(cp, cp, 0x3232);
      o[0] *= a0; o[1] *= a0; o[4] *= a0; o[5] *= a0; o[8] *= a0;
      o[2] *= a1; o[3] *= a1; o[6] *= a1; o[7] *= a1; o[10] *= a1;
#pragma unroll
      for (int grp = 0; grp < 4; grp++) {
#pragma unroll
        for (int i = grp * 16; i < grp * 16 + 16; i++)
          s[i] = is_poly(i) ? exp2_fma(s[i], (i & 1) ? p1 : p0) : h_ex2(h_add(s[i], (i & 1) ? c1 : c0));
        wg_fence();
#pragma unroll
        for (int ks = grp * 4; ks < grp * 4 + 4; ks++) mma_pv24(o, s + ks * 4, dv0 + kb * 256, ks * 256, 1);
      }
      wg_commit();
      wg_wait<0>();
      reg_fence<12>(o);
    }
    const float i0 = 1.f / o[8], i1 = 1.f / o[10];
    g_attn[(rb16 * 32 + head) * 32 + lane] = make_uint4(pack_bf16(o[0] * i0, o[1] * i0), pack_bf16(o[2] * i1, o[3] * i1),
                                                        pack_bf16(o[4] * i0, o[5] * i0), pack_bf16(o[6] * i1, o[7] * i1));
  }
}

__device__ float4 g_stats[128 * 16 * 4];
constexpr int NST = 13, STB = 16384;
constexpr int FFN_SMEM = NST * STB + 4096 + 512 + 1024;

__device__ __forceinline__ void flag_signal(unsigned* f, int lane) {
  __syncwarp();
  if (lane == 0) asm volatile("red.release.gpu.global.add.u32 [%0], 1;" ::"l"(f) : "memory");
}
__device__ __forceinline__ void flag_wait(const unsigned* f, int lane) {
  if (lane == 0) {
    unsigned v, n = 0;
    do {
      asm volatile("ld.acquire.gpu.global.u32 %0, [%1];" : "=r"(v) : "l"(f) : "memory");
      if (++n > (1u << 24)) __trap();
    } while (v < 8);
  }
  __syncwarp();
}
__device__ __forceinline__ float silu_mul(float g, float u) { return g * u * rcpf(1.f + ex2f(g * -1.4426950408889634f)); }

__global__ void __launch_bounds__(384, 1) __cluster_dims__(2, 1, 1)
k_ffn(const __grid_constant__ CUtensorMap tm_wo, const __grid_constant__ CUtensorMap tm_w1, const __grid_constant__ CUtensorMap tm_w3,
      const __grid_constant__ CUtensorMap tm_w2, const bf16* __restrict__ x, bf16* __restrict__ out) {
  extern __shared__ __align__(1024) uint8_t sp[];
  const uint32_t sb = smem_u32(sp), dlo = desc_lo(sb, 8192);
  if (sb & 1023) __trap();
  const uint32_t bfull = sb + NST * STB + 4096, bempty = bfull + 8 * NST, bpeer = bempty + 8 * NST, bx = bpeer + 8;
  const int tid = threadIdx.x, lane = tid & 31, w = tid >> 5;
  const int j = blockIdx.x & 7, rb = blockIdx.x >> 3, kh = j & 1;
  if (tid == 0) {
    for (int i = 0; i < NST; i++) { mbar_init(bfull + 8 * i, 1); mbar_init(bempty + 8 * i, 8); }
    mbar_init(bpeer, 8);
    for (int i = 0; i < 8; i++) { mbar_init(bx + 8 * i, 1); }
    asm volatile("fence.mbarrier_init.release.cluster;" ::: "memory");
    for (int i = 0; i < 8; i++) mbar_expect(bx + 8 * i, 4096);
  }
  if (tid < 256) *(uint4*)(sp + NST * STB + tid * 16) = ldg128((const uint8_t*)g_mod + 2048 + tid * 16);
  __syncthreads();
  asm volatile("barrier.cluster.arrive.release.aligned;" ::: "memory");
  if (w >= 8) {
    asm volatile("setmaxnreg.dec.sync.aligned.u32 24;");
    if (tid == 256) {
      int slot = 0, ph = 1;
#pragma unroll 1
      for (int st = 0; st < 39; st++) {
        const CUtensorMap *m0, *m1; int x0, y0, x1, y1;
        if (st < 4) { m0 = m1 = &tm_wo; x0 = x1 = j * 64; y0 = st * 128; y1 = y0 + 64; }
        else if (st < 28) { m0 = &tm_w1; m1 = &tm_w3; x0 = x1 = j * 176 + ((st - 4) >> 3) * 64; y0 = y1 = ((st - 4) & 7) * 64; }
        else { m0 = m1 = &tm_w2; x0 = (j >> 1) * 128; x1 = x0 + 64; y0 = y1 = kh * 688 + (st - 28) * 64; }
        mbar_wait(bempty + 8 * slot, ph);
        mbar_expect(bfull + 8 * slot, STB);
        tma2d(sb + slot * STB, m0, x0, y0, bfull + 8 * slot);
        tma2d(sb + slot * STB + 8192, m1, x1, y1, bfull + 8 * slot);
        if (++slot == NST) { slot = 0; ph ^= 1; }
      }
    }
    __syncwarp();
    asm volatile("barrier.cluster.wait.acquire.aligned;" ::: "memory");
  } else {
    asm volatile("setmaxnreg.inc.sync.aligned.u32 240;");
    const int g = lane >> 2, q = lane & 3, rb16 = rb * 8 + w;
    const uint32_t* smod = (const uint32_t*)(sp + NST * STB);
    uint32_t a[128];
    float acc[64];
    uint32_t xr[16];
    {
      const uint32_t* x0 = (const uint32_t*)(x + (size_t)(rb16 * 16 + g) * D_ + j * 64) + q;
#pragma unroll
      for (int i = 0; i < 8; i++) { xr[2 * i] = __ldg(x0 + i * 4); xr[2 * i + 1] = __ldg(x0 + 8 * D_ / 2 + i * 4); }
    }
    asm volatile("barrier.cluster.wait.acquire.aligned;" ::: "memory");
    pdl_wait();
#pragma unroll
    for (int i = 0; i < 32; i++) { uint4 u = ldg128(g_attn + (rb16 * 32 + i) * 32 + lane); a[4 * i] = u.x; a[4 * i + 1] = u.y; a[4 * i + 2] = u.z; a[4 * i + 3] = u.w; }
#pragma unroll
    for (int st = 0; st < 4; st++) {
      mbar_wait(bfull + 8 * st, 0);
      wg_fence();
#pragma unroll
      for (int ks = 0; ks < 8; ks++) MMA(mma_n64, st * STB + ks * 2048, st | ks, acc, a + (st * 8 + ks) * 4, dlo);
    }
    wg_commit();
    wg_wait<0>();
    reg_fence<32>(acc);
    if (lane < 4) mbar_arrive(bempty + 8 * lane);
    {
      float s0 = 0.f, s1 = 0.f;
#pragma unroll
      for (int i = 0; i < 8; i++) {
        const uint32_t ga = smod[j * 32 + i * 4 + q];
        xr[2 * i] = pack_bf16(bf_lo(xr[2 * i]) + bf_lo(ga) * acc[4 * i], bf_hi(xr[2 * i]) + bf_hi(ga) * acc[4 * i + 1]);
        xr[2 * i + 1] = pack_bf16(bf_lo(xr[2 * i + 1]) + bf_lo(ga) * acc[4 * i + 2], bf_hi(xr[2 * i + 1]) + bf_hi(ga) * acc[4 * i + 3]);
        s0 += bf_lo(xr[2 * i]) + bf_hi(xr[2 * i]); s1 += bf_lo(xr[2 * i + 1]) + bf_hi(xr[2 * i + 1]);
      }
#pragma unroll
      for (int i = 0; i < 4; i++) g_x1[(rb16 * 32 + j * 4 + i) * 32 + lane] = make_uint4(xr[4 * i], xr[4 * i + 1], xr[4 * i + 2], xr[4 * i + 3]);
      s0 += __shfl_xor_sync(~0u, s0, 1); s1 += __shfl_xor_sync(~0u, s1, 1);
      s0 += __shfl_xor_sync(~0u, s0, 2); s1 += __shfl_xor_sync(~0u, s1, 2);
      s0 *= 1.f / 64; s1 *= 1.f / 64;
      float v0 = 0.f, v1 = 0.f;
#pragma unroll
      for (int i = 0; i < 8; i++) {
        float d = bf_lo(xr[2 * i]) - s0; v0 += d * d; d = bf_hi(xr[2 * i]) - s0; v0 += d * d;
        d = bf_lo(xr[2 * i + 1]) - s1; v1 += d * d; d = bf_hi(xr[2 * i + 1]) - s1; v1 += d * d;
      }
      v0 += __shfl_xor_sync(~0u, v0, 1); v1 += __shfl_xor_sync(~0u, v1, 1);
      v0 += __shfl_xor_sync(~0u, v0, 2); v1 += __shfl_xor_sync(~0u, v1, 2);
      if (q < 2) ((float2*)g_stats)[(rb16 * 16 + g + q * 8) * 8 + j] = q ? make_float2(s1, v1) : make_float2(s0, v0);
    }
    flag_signal(g_flags + rb16 * 8, lane);
    flag_wait(g_flags + rb16 * 8, lane);
    uint32_t r0, r1, n0, n1;
    {
      uint4 t0 = ldg128(g_stats + (rb16 * 16 + g) * 4 + q), t1 = ldg128(g_stats + (rb16 * 16 + g + 8) * 4 + q);
#pragma unroll
      for (int i = 0; i < 32; i++) { uint4 u = ldg128(g_x1 + (rb16 * 32 + i) * 32 + lane); a[4 * i] = u.x; a[4 * i + 1] = u.y; a[4 * i + 2] = u.z; a[4 * i + 3] = u.w; }
      float m0 = __uint_as_float(t0.x) + __uint_as_float(t0.z), m1 = __uint_as_float(t1.x) + __uint_as_float(t1.z);
      m0 += __shfl_xor_sync(~0u, m0, 1); m1 += __shfl_xor_sync(~0u, m1, 1);
      m0 += __shfl_xor_sync(~0u, m0, 2); m1 += __shfl_xor_sync(~0u, m1, 2);
      m0 *= 0.125f; m1 *= 0.125f;
      float d0 = __uint_as_float(t0.x) - m0, d1 = __uint_as_float(t0.z) - m0;
      float v0 = __uint_as_float(t0.y) + __uint_as_float(t0.w) + 64.f * (d0 * d0 + d1 * d1);
      d0 = __uint_as_float(t1.x) - m1; d1 = __uint_as_float(t1.z) - m1;
      float v1 = __uint_as_float(t1.y) + __uint_as_float(t1.w) + 64.f * (d0 * d0 + d1 * d1);
      v0 += __shfl_xor_sync(~0u, v0, 1); v1 += __shfl_xor_sync(~0u, v1, 1);
      v0 += __shfl_xor_sync(~0u, v0, 2); v1 += __shfl_xor_sync(~0u, v1, 2);
      v0 = rsqrtf(v0 * (1.f / D_) + 1e-5f); v1 = rsqrtf(v1 * (1.f / D_) + 1e-5f);
      r0 = pack_bf16(v0, v0); r1 = pack_bf16(v1, v1);
      m0 *= -bf_lo(r0); m1 *= -bf_lo(r1);
      n0 = pack_bf16(m0, m0); n1 = pack_bf16(m1, m1);
    }
#pragma unroll
    for (int p = 0; p < 3; p++) {
#pragma unroll
      for (int kb = 0; kb < 8; kb++) {
        const int st = 4 + p * 8 + kb, slot = st % NST;
        if (p == 0) {
#pragma unroll
          for (int i = kb * 8; i < kb * 8 + 8; i++) {
            const uint32_t sv = smod[256 + i * 4 + q], cv = smod[512 + i * 4 + q];
            a[2 * i] = bf_fma2(bf_fma2(a[2 * i], r0, n0), cv, sv);
            a[2 * i + 1] = bf_fma2(bf_fma2(a[2 * i + 1], r1, n1), cv, sv);
          }
        }
        mbar_wait(bfull + 8 * slot, (st / NST) & 1);
        wg_fence();
#pragma unroll
        for (int ks = 0; ks < 4; ks++) {
          if (p < 2) MMA(mma_n128, slot * STB + ks * 2048, kb | ks, acc, a + (kb * 4 + ks) * 4, dlo);
          else {
            MMA(mma_n48, slot * STB + ks * 2048, kb | ks, acc, a + (kb * 4 + ks) * 4, dlo);
            MMA(mma_n48, slot * STB + 8192 + ks * 2048, kb | ks, acc + 32, a + (kb * 4 + ks) * 4, dlo);
          }
        }
        wg_commit();
        if (kb > 0) { wg_wait<1>(); if (lane == 0) mbar_arrive(bempty + 8 * ((st - 1) % NST)); }
      }
      wg_wait<0>();
      reg_fence<64>(acc);
      if (lane == 0) {
        mbar_arrive(bempty + 8 * ((4 + p * 8 + 7) % NST));
        if (p == 2) {
          uint32_t ra; asm volatile("mapa.shared::cluster.u32 %0, %1, %2;" : "=r"(ra) : "r"(bpeer), "r"(kh ^ 1));
          asm volatile("mbarrier.arrive.shared::cluster.b64 _, [%0];" ::"r"(ra) : "memory");
        }
      }
#pragma unroll
      for (int ks = 0; ks < (p < 2 ? 4 : 3); ks++) {
        const int kk = j * 11 + p * 4 + ks;
        const float* gt = acc + 8 * ks; const float* up = acc + 32 + 8 * ks;
        uint4 u = make_uint4(pack_bf16(silu_mul(gt[0], up[0]), silu_mul(gt[1], up[1])), pack_bf16(silu_mul(gt[2], up[2]), silu_mul(gt[3], up[3])),
                             pack_bf16(silu_mul(gt[4], up[4]), silu_mul(gt[5], up[5])), pack_bf16(silu_mul(gt[6], up[6]), silu_mul(gt[7], up[7])));
        if (kk < KS_F) g_act[(rb16 * KS_F + kk) * 32 + lane] = u;
      }
    }
    flag_signal(g_flags + 1024 + rb16 * 8, lane);
    flag_wait(g_flags + 1024 + rb16 * 8, lane);
    const uint4* ap = g_act + (rb16 * KS_F + kh * 43) * 32 + lane;
#pragma unroll
    for (int i = 0; i < 32; i++) { uint4 u = ldg128(ap + i * 32); a[4 * i] = u.x; a[4 * i + 1] = u.y; a[4 * i + 2] = u.z; a[4 * i + 3] = u.w; }
#pragma unroll
    for (int kb = 0; kb < 11; kb++) {
      const int slot = (28 + kb) % NST;
      mbar_wait(bfull + 8 * slot, 0);
      wg_fence();
#pragma unroll
      for (int ks = 0; ks < (kb < 10 ? 4 : 3); ks++)
        MMA(mma_n128, slot * STB + ks * 2048, kb | ks, acc, a + ((kb * 4 + ks) & 31) * 4, dlo);
      wg_commit();
      if (kb == 2) {
        wg_wait<0>();
        reg_fence<64>(acc);
#pragma unroll
        for (int i = 0; i < 11; i++) { uint4 u = ldg128(ap + (32 + i) * 32); a[4 * i] = u.x; a[4 * i + 1] = u.y; a[4 * i + 2] = u.z; a[4 * i + 3] = u.w; }
      }
    }
#pragma unroll
    for (int i = 0; i < 4; i++) { uint4 u = ldg128(g_x1 + (rb16 * 32 + j * 4 + i) * 32 + lane); xr[4 * i] = u.x; xr[4 * i + 1] = u.y; xr[4 * i + 2] = u.z; xr[4 * i + 3] = u.w; }
    mbar_wait_cluster(bpeer, 0);
    wg_wait<0>();
    reg_fence<64>(acc);
    {
      uint32_t ra, rbar;
      asm volatile("mapa.shared::cluster.u32 %0, %1, %2;" : "=r"(ra) : "r"(sb + tid * 16), "r"(kh ^ 1));
      asm volatile("mapa.shared::cluster.u32 %0, %1, %2;" : "=r"(rbar) : "r"(bx + 8 * w), "r"(kh ^ 1));
#pragma unroll
      for (int i = 0; i < 8; i++) {
        const float s0 = kh ? acc[4 * i] : acc[32 + 4 * i], s1 = kh ? acc[4 * i + 1] : acc[33 + 4 * i];
        const float s2 = kh ? acc[4 * i + 2] : acc[34 + 4 * i], s3 = kh ? acc[4 * i + 3] : acc[35 + 4 * i];
        asm volatile("st.async.weak.shared::cluster.mbarrier::complete_tx::bytes.v4.f32 [%0], {%1,%2,%3,%4}, [%5];"
                     ::"r"(ra + i * 4096), "f"(s0), "f"(s1), "f"(s2), "f"(s3), "r"(rbar) : "memory");
      }
    }
    mbar_wait_cluster(bx + 8 * w, 0);
    uint32_t* o0 = (uint32_t*)(out + (size_t)(rb16 * 16 + g) * D_ + j * 64) + q;
#pragma unroll
    for (int i = 0; i < 8; i++) {
      const float4 pv = *(const float4*)(sp + i * 4096 + tid * 16);
      const uint32_t gb = smod[768 + j * 32 + i * 4 + q];
      const float s0 = (kh ? acc[32 + 4 * i] : acc[4 * i]) + pv.x, s1 = (kh ? acc[33 + 4 * i] : acc[4 * i + 1]) + pv.y;
      const float s2 = (kh ? acc[34 + 4 * i] : acc[4 * i + 2]) + pv.z, s3 = (kh ? acc[35 + 4 * i] : acc[4 * i + 3]) + pv.w;
      o0[i * 4] = pack_bf16(bf_lo(xr[2 * i]) + bf_lo(gb) * s0, bf_hi(xr[2 * i]) + bf_hi(gb) * s1);
      o0[8 * D_ / 2 + i * 4] = pack_bf16(bf_lo(xr[2 * i + 1]) + bf_lo(gb) * s2, bf_hi(xr[2 * i + 1]) + bf_hi(gb) * s3);
    }
  }
}

typedef CUresult (*EncodeFn)(CUtensorMap*, CUtensorMapDataType, cuuint32_t, void*, const cuuint64_t*, const cuuint64_t*,
                             const cuuint32_t*, const cuuint32_t*, CUtensorMapInterleave, CUtensorMapSwizzle,
                             CUtensorMapL2promotion, CUtensorMapFloatOOBfill);
static void make_map(EncodeFn enc, CUtensorMap* m, const void* p, int rank, const cuuint64_t* dims, const cuuint64_t* strides, const cuuint32_t* box) {
  const cuuint32_t es[5] = {1, 1, 1, 1, 1};
  enc(m, CU_TENSOR_MAP_DATA_TYPE_BFLOAT16, rank, (void*)p, dims, strides, box, es, CU_TENSOR_MAP_INTERLEAVE_NONE,
      CU_TENSOR_MAP_SWIZZLE_128B, CU_TENSOR_MAP_L2_PROMOTION_L2_256B, CU_TENSOR_MAP_FLOAT_OOB_FILL_NONE);
}
static void make_map2(EncodeFn enc, CUtensorMap* m, const void* p, int cols, int rows) {
  const cuuint64_t dims[2] = {(cuuint64_t)cols, (cuuint64_t)rows}, st[1] = {(cuuint64_t)cols * 2};
  const cuuint32_t box[2] = {64, 64};
  make_map(enc, m, p, 2, dims, st, box);
}
template <typename... KA, typename... A>
static void launch(void (*k)(KA...), int grid, int block, int smem, bool pdl, A... args) {
  cudaLaunchConfig_t cfg = {};
  cfg.gridDim = dim3(grid); cfg.blockDim = dim3(block); cfg.dynamicSmemBytes = smem; cfg.stream = cudaStreamPerThread;
  cudaLaunchAttribute at[1];
  at[0].id = cudaLaunchAttributeProgrammaticStreamSerialization;
  at[0].val.programmaticStreamSerializationAllowed = 1;
  cfg.attrs = at; cfg.numAttrs = pdl ? 1 : 0;
  cudaLaunchKernelEx(&cfg, k, KA(args)...);
}

extern "C" void kernel_launch(void* const* d_in, const int* in_sizes, int n_in, void* d_out, int out_size) {
  const bf16 *x = (const bf16*)d_in[0], *wqkv = (const bf16*)d_in[1], *wo = (const bf16*)d_in[2];
  const bf16 *w1 = (const bf16*)d_in[4], *w3 = (const bf16*)d_in[5], *w2 = (const bf16*)d_in[6];
  const bf16 *c = (const bf16*)d_in[7], *wm = (const bf16*)d_in[8];
  void* fn = nullptr;
  cudaDriverEntryPointQueryResult qr;
  cudaGetDriverEntryPoint("cuTensorMapEncodeTiled", &fn, cudaEnableDefault, &qr);
  EncodeFn enc = (EncodeFn)fn;
  CUtensorMap m_qkv, m_o, m_1, m_3, m_2;
  {
    const cuuint64_t rs = 3 * D_ * 2, dims[5] = {3 * D_, 2, 4, 4, 16}, st[4] = {rs, 8 * rs, 2 * rs, 32 * rs};
    const cuuint32_t box[5] = {64, 2, 4, 4, 2};
    make_map(enc, &m_qkv, wqkv, 5, dims, st, box);
  }
  make_map2(enc, &m_o, wo, D_, D_);
  make_map2(enc, &m_1, w1, F_, D_);
  make_map2(enc, &m_3, w3, F_, D_);
  make_map2(enc, &m_2, w2, D_, F_);
  cudaFuncSetAttribute(k_qkv, cudaFuncAttributeMaxDynamicSharedMemorySize, QKV_SMEM);
  cudaFuncSetAttribute(k_attn, cudaFuncAttributeMaxDynamicSharedMemorySize, ATT_SMEM);
  cudaFuncSetAttribute(k_ffn, cudaFuncAttributeMaxDynamicSharedMemorySize, FFN_SMEM);
  launch(k_mod, 96, 256, 0, false, c, wm);
  launch(k_qkv, 128, 256, QKV_SMEM, true, m_qkv, x);
  launch(k_attn, 128, 512, ATT_SMEM, true, wo, w1, w3, w2);
  launch(k_ffn, 128, 384, FFN_SMEM, true, m_o, m_1, m_3, m_2, x, (bf16*)d_out);
}
```

```cpp
#include <cuda_runtime.h>
#include <cuda_bf16.h>
#include <cuda_fp16.h>
#include <cuda.h>
#include <stdint.h>

typedef __nv_bfloat16 bf16;
constexpr int S_ = 2048, D_ = 512, F_ = 1376, NH = 32;
constexpr int KS_F = F_ / 16;

__device__ __align__(16) bf16 g_mod[6 * D_];
__device__ uint4 g_q[NH * 128 * 32];
__device__ uint4 g_k[NH * 2 * S_];
__device__ uint4 g_v[NH * 2 * S_];
__device__ uint4 g_attn[128 * 32 * 32];
__device__ uint4 g_x1[128 * 32 * 32];
__device__ uint4 g_act[128 * KS_F * 32];
__device__ unsigned g_flags[2 * 128 * 8];

__device__ __forceinline__ uint32_t smem_u32(const void* p) { return (uint32_t)__cvta_generic_to_shared(p); }
__device__ __forceinline__ void mbar_init(uint32_t b, uint32_t n) { asm volatile("mbarrier.init.shared::cta.b64 [%0], %1;" ::"r"(b), "r"(n) : "memory"); }
__device__ __forceinline__ void mbar_expect(uint32_t b, uint32_t bytes) { asm volatile("mbarrier.arrive.expect_tx.shared::cta.b64 _, [%0], %1;" ::"r"(b), "r"(bytes) : "memory"); }
__device__ __forceinline__ void mbar_arrive(uint32_t b) { asm volatile("mbarrier.arrive.shared::cta.b64 _, [%0];" ::"r"(b) : "memory"); }
__device__ __forceinline__ void mbar_wait(uint32_t b, uint32_t ph) {
  asm volatile("{.reg .pred p; .reg .u32 n; mov.u32 n, 0;\n"
               "W: mbarrier.try_wait.parity.shared::cta.b64 p, [%0], %1;\n"
               "@p bra D; add.u32 n, n, 1; setp.lt.u32 p, n, 0x4000000; @p bra W;\n"
               "D: }" ::"r"(b), "r"(ph) : "memory");
}
__device__ __forceinline__ void mbar_wait_cluster(uint32_t b, uint32_t ph) {
  asm volatile("{.reg .pred p; .reg .u32 n; mov.u32 n, 0;\n"
               "W: mbarrier.try_wait.parity.acquire.cluster.shared::cta.b64 p, [%0], %1;\n"
               "@p bra D; add.u32 n, n, 1; setp.lt.u32 p, n, 0x4000000; @p bra W;\n"
               "D: }" ::"r"(b), "r"(ph) : "memory");
}
__device__ __forceinline__ void tma2d(uint32_t dst, const CUtensorMap* m, int c0, int c1, uint32_t bar) {
  asm volatile("cp.async.bulk.tensor.2d.shared::cluster.global.mbarrier::complete_tx::bytes [%0], [%1, {%3, %4}], [%2];"
               ::"r"(dst), "l"(m), "r"(bar), "r"(c0), "r"(c1) : "memory");
}
__device__ __forceinline__ void tma5d(uint32_t dst, const CUtensorMap* m, int c0, int c4, uint32_t bar) {
  asm volatile("cp.async.bulk.tensor.5d.shared::cluster.global.mbarrier::complete_tx::bytes [%0], [%1, {%3, 0, 0, 0, %4}], [%2];"
               ::"r"(dst), "l"(m), "r"(bar), "r"(c0), "r"(c4) : "memory");
}
__device__ __forceinline__ void bulk_g2s(uint32_t dst, const void* src, uint32_t bytes, uint32_t bar) {
  asm volatile("cp.async.bulk.shared::cluster.global.mbarrier::complete_tx::bytes [%0], [%1], %2, [%3];"
               ::"r"(dst), "l"(src), "r"(bytes), "r"(bar) : "memory");
}
__device__ __forceinline__ void l2_prefetch(const void* src, uint32_t bytes) {
  asm volatile("cp.async.bulk.prefetch.L2.global [%0], %1;" ::"l"(src), "r"(bytes) : "memory");
}
__device__ __forceinline__ void pdl_wait() { asm volatile("griddepcontrol.wait;" ::: "memory"); }
__device__ __forceinline__ void pdl_trigger() { asm volatile("griddepcontrol.launch_dependents;" ::: "memory"); }
__device__ __forceinline__ void wg_fence() { asm volatile("wgmma.fence.sync.aligned;" ::: "memory"); }
__device__ __forceinline__ void wg_commit() { asm volatile("wgmma.commit_group.sync.aligned;" ::: "memory"); }
template <int N> __device__ __forceinline__ void wg_wait() { asm volatile("wgmma.wait_group.sync.aligned %0;" ::"n"(N) : "memory"); }
template <int N> __device__ __forceinline__ void reg_fence(float* r) {
#pragma unroll
  for (int i = 0; i < N; i++) asm volatile("" : "+f"(r[i])::"memory");
}
template <int N> __device__ __forceinline__ void reg_fence(uint32_t* r) {
#pragma unroll
  for (int i = 0; i < N; i++) asm volatile("" : "+r"(r[i])::"memory");
}
__device__ __forceinline__ uint4 ldg128(const void* p) {
  uint4 v; asm volatile("ld.global.L1::no_allocate.v4.u32 {%0,%1,%2,%3}, [%4];" : "=r"(v.x), "=r"(v.y), "=r"(v.z), "=r"(v.w) : "l"(p) : "memory"); return v;
}
__device__ __forceinline__ uint4 ldg128_nc(const void* p) {
  uint4 v; asm volatile("ld.global.nc.L1::no_allocate.v4.u32 {%0,%1,%2,%3}, [%4];" : "=r"(v.x), "=r"(v.y), "=r"(v.z), "=r"(v.w) : "l"(p)); return v;
}
__device__ __forceinline__ uint32_t pack_bf16(float lo, float hi) { uint32_t r; asm("cvt.rn.bf16x2.f32 %0, %1, %2;" : "=r"(r) : "f"(hi), "f"(lo)); return r; }
__device__ __forceinline__ uint32_t pack_f16(float lo, float hi) { uint32_t r; asm("cvt.rn.satfinite.f16x2.f32 %0, %1, %2;" : "=r"(r) : "f"(hi), "f"(lo)); return r; }
__device__ __forceinline__ float bf_lo(uint32_t v) { return __uint_as_float(v << 16); }
__device__ __forceinline__ float bf_hi(uint32_t v) { return __uint_as_float(v & 0xffff0000u); }
__device__ __forceinline__ uint32_t bf_fma2(uint32_t a, uint32_t b, uint32_t c) { uint32_t r; asm("fma.rn.bf16x2 %0, %1, %2, %3;" : "=r"(r) : "r"(a), "r"(b), "r"(c)); return r; }
__device__ __forceinline__ float ex2f(float x) { float r; asm("ex2.approx.ftz.f32 %0, %1;" : "=f"(r) : "f"(x)); return r; }
__device__ __forceinline__ float rcpf(float x) { float r; asm("rcp.approx.ftz.f32 %0, %1;" : "=f"(r) : "f"(x)); return r; }
__device__ __forceinline__ uint32_t desc_lo(uint32_t addr, uint32_t lbo) { return ((addr & 0x3FFFF) >> 4) | ((lbo >> 4) << 16); }
#define MMA(fn, off, accum, d, a, dlo) fn(d, a, dlo, off, accum)
__device__ __forceinline__ uint64_t desc_plain(uint32_t addr, uint32_t lbo, uint32_t sbo) {
  return (uint64_t)((addr & 0x3FFFF) >> 4) | ((uint64_t)(lbo >> 4) << 16) | ((uint64_t)(sbo >> 4) << 32);
}
__device__ __forceinline__ void mma_n64(float* d, const uint32_t* a, uint32_t dlo, int off, int acc) {
  asm volatile("{.reg .pred p; .reg .b32 t; .reg .b64 ds; add.u32 t, %36, %37; mov.b64 ds, {t, 0x40000040}; setp.ne.b32 p, %38, 0;\n"
    "wgmma.mma_async.sync.aligned.m64n64k16.f32.bf16.bf16 {%0,%1,%2,%3,%4,%5,%6,%7,%8,%9,%10,%11,%12,%13,%14,%15,%16,%17,%18,%19,%20,%21,%22,%23,%24,%25,%26,%27,%28,%29,%30,%31}, "
    "{%32,%33,%34,%35}, ds, p, 1, 1, 1;}"
    : "+f"(d[0]),"+f"(d[1]),"+f"(d[2]),"+f"(d[3]),"+f"(d[4]),"+f"(d[5]),"+f"(d[6]),"+f"(d[7]),"+f"(d[8]),"+f"(d[9]),"+f"(d[10]),"+f"(d[11]),"+f"(d[12]),"+f"(d[13]),"+f"(d[14]),"+f"(d[15]),"+f"(d[16]),"+f"(d[17]),"+f"(d[18]),"+f"(d[19]),"+f"(d[20]),"+f"(d[21]),"+f"(d[22]),"+f"(d[23]),"+f"(d[24]),"+f"(d[25]),"+f"(d[26]),"+f"(d[27]),"+f"(d[28]),"+f"(d[29]),"+f"(d[30]),"+f"(d[31])
    : "r"(a[0]), "r"(a[1]), "r"(a[2]), "r"(a[3]), "r"(dlo), "r"(off >> 4), "r"(acc));
}
__device__ __forceinline__ void mma_n128(float* d, const uint32_t* a, uint32_t dlo, int off, int acc) {
  asm volatile("{.reg .pred p; .reg .b32 t; .reg .b64 ds; add.u32 t, %68, %69; mov.b64 ds, {t, 0x40000040}; setp.ne.b32 p, %70, 0;\n"
    "wgmma.mma_async.sync.aligned.m64n128k16.f32.bf16.bf16 {%0,%1,%2,%3,%4,%5,%6,%7,%8,%9,%10,%11,%12,%13,%14,%15,%16,%17,%18,%19,%20,%21,%22,%23,%24,%25,%26,%27,%28,%29,%30,%31,%32,%33,%34,%35,%36,%37,%38,%39,%40,%41,%42,%43,%44,%45,%46,%47,%48,%49,%50,%51,%52,%53,%54,%55,%56,%57,%58,%59,%60,%61,%62,%63}, "
    "{%64,%65,%66,%67}, ds, p, 1, 1, 1;}"
    : "+f"(d[0]),"+f"(d[1]),"+f"(d[2]),"+f"(d[3]),"+f"(d[4]),"+f"(d[5]),"+f"(d[6]),"+f"(d[7]),"+f"(d[8]),"+f"(d[9]),"+f"(d[10]),"+f"(d[11]),"+f"(d[12]),"+f"(d[13]),"+f"(d[14]),"+f"(d[15]),"+f"(d[16]),"+f"(d[17]),"+f"(d[18]),"+f"(d[19]),"+f"(d[20]),"+f"(d[21]),"+f"(d[22]),"+f"(d[23]),"+f"(d[24]),"+f"(d[25]),"+f"(d[26]),"+f"(d[27]),"+f"(d[28]),"+f"(d[29]),"+f"(d[30]),"+f"(d[31]),"+f"(d[32]),"+f"(d[33]),"+f"(d[34]),"+f"(d[35]),"+f"(d[36]),"+f"(d[37]),"+f"(d[38]),"+f"(d[39]),"+f"(d[40]),"+f"(d[41]),"+f"(d[42]),"+f"(d[43]),"+f"(d[44]),"+f"(d[45]),"+f"(d[46]),"+f"(d[47]),"+f"(d[48]),"+f"(d[49]),"+f"(d[50]),"+f"(d[51]),"+f"(d[52]),"+f"(d[53]),"+f"(d[54]),"+f"(d[55]),"+f"(d[56]),"+f"(d[57]),"+f"(d[58]),"+f"(d[59]),"+f"(d[60]),"+f"(d[61]),"+f"(d[62]),"+f"(d[63])
    : "r"(a[0]), "r"(a[1]), "r"(a[2]), "r"(a[3]), "r"(dlo), "r"(off >> 4), "r"(acc));
}
__device__ __forceinline__ void mma_n48(float* d, const uint32_t* a, uint32_t dlo, int off, int acc) {
  asm volatile("{.reg .pred p; .reg .b32 t; .reg .b64 ds; add.u32 t, %28, %29; mov.b64 ds, {t, 0x40000040}; setp.ne.b32 p, %30, 0;\n"
    "wgmma.mma_async.sync.aligned.m64n48k16.f32.bf16.bf16 {%0,%1,%2,%3,%4,%5,%6,%7,%8,%9,%10,%11,%12,%13,%14,%15,%16,%17,%18,%19,%20,%21,%22,%23}, "
    "{%24,%25,%26,%27}, ds, p, 1, 1, 1;}"
    : "+f"(d[0]),"+f"(d[1]),"+f"(d[2]),"+f"(d[3]),"+f"(d[4]),"+f"(d[5]),"+f"(d[6]),"+f"(d[7]),"+f"(d[8]),"+f"(d[9]),"+f"(d[10]),"+f"(d[11]),"+f"(d[12]),"+f"(d[13]),"+f"(d[14]),"+f"(d[15]),"+f"(d[16]),"+f"(d[17]),"+f"(d[18]),"+f"(d[19]),"+f"(d[20]),"+f"(d[21]),"+f"(d[22]),"+f"(d[23])
    : "r"(a[0]), "r"(a[1]), "r"(a[2]), "r"(a[3]), "r"(dlo), "r"(off >> 4), "r"(acc));
}
__device__ __forceinline__ void mma_pv24(float* d, const uint32_t* a, uint32_t dlo, int off, int acc) {
  asm volatile("{.reg .pred p; .reg .b32 t; .reg .b64 ds; add.u32 t, %16, %17; mov.b64 ds, {t, 0x800}; setp.ne.b32 p, %18, 0;\n"
    "wgmma.mma_async.sync.aligned.m64n24k16.f32.f16.f16 {%0,%1,%2,%3,%4,%5,%6,%7,%8,%9,%10,%11}, "
    "{%12,%13,%14,%15}, ds, p, 1, 1, 1;}"
    : "+f"(d[0]),"+f"(d[1]),"+f"(d[2]),"+f"(d[3]),"+f"(d[4]),"+f"(d[5]),"+f"(d[6]),"+f"(d[7]),"+f"(d[8]),"+f"(d[9]),"+f"(d[10]),"+f"(d[11])
    : "r"(a[0]), "r"(a[1]), "r"(a[2]), "r"(a[3]), "r"(dlo), "r"(off >> 4), "r"(acc));
}
__device__ __forceinline__ void mma_qk256(uint32_t* d, const uint32_t* a, uint64_t desc) {
  asm volatile("wgmma.mma_async.sync.aligned.m64n256k16.f16.f16.f16 {%0,%1,%2,%3,%4,%5,%6,%7,%8,%9,%10,%11,%12,%13,%14,%15,%16,%17,%18,%19,%20,%21,%22,%23,%24,%25,%26,%27,%28,%29,%30,%31,%32,%33,%34,%35,%36,%37,%38,%39,%40,%41,%42,%43,%44,%45,%46,%47,%48,%49,%50,%51,%52,%53,%54,%55,%56,%57,%58,%59,%60,%61,%62,%63}, "
    "{%64,%65,%66,%67}, %68, 0, 1, 1, 0;"
    : "=r"(d[0]),"=r"(d[1]),"=r"(d[2]),"=r"(d[3]),"=r"(d[4]),"=r"(d[5]),"=r"(d[6]),"=r"(d[7]),"=r"(d[8]),"=r"(d[9]),"=r"(d[10]),"=r"(d[11]),"=r"(d[12]),"=r"(d[13]),"=r"(d[14]),"=r"(d[15]),"=r"(d[16]),"=r"(d[17]),"=r"(d[18]),"=r"(d[19]),"=r"(d[20]),"=r"(d[21]),"=r"(d[22]),"=r"(d[23]),"=r"(d[24]),"=r"(d[25]),"=r"(d[26]),"=r"(d[27]),"=r"(d[28]),"=r"(d[29]),"=r"(d[30]),"=r"(d[31]),"=r"(d[32]),"=r"(d[33]),"=r"(d[34]),"=r"(d[35]),"=r"(d[36]),"=r"(d[37]),"=r"(d[38]),"=r"(d[39]),"=r"(d[40]),"=r"(d[41]),"=r"(d[42]),"=r"(d[43]),"=r"(d[44]),"=r"(d[45]),"=r"(d[46]),"=r"(d[47]),"=r"(d[48]),"=r"(d[49]),"=r"(d[50]),"=r"(d[51]),"=r"(d[52]),"=r"(d[53]),"=r"(d[54]),"=r"(d[55]),"=r"(d[56]),"=r"(d[57]),"=r"(d[58]),"=r"(d[59]),"=r"(d[60]),"=r"(d[61]),"=r"(d[62]),"=r"(d[63])
    : "r"(a[0]), "r"(a[1]), "r"(a[2]), "r"(a[3]), "l"(desc));
}
__device__ __forceinline__ void mma_qk128(uint32_t* d, const uint32_t* a, uint64_t desc) {
  asm volatile("wgmma.mma_async.sync.aligned.m64n128k16.f16.f16.f16 {%0,%1,%2,%3,%4,%5,%6,%7,%8,%9,%10,%11,%12,%13,%14,%15,%16,%17,%18,%19,%20,%21,%22,%23,%24,%25,%26,%27,%28,%29,%30,%31}, "
    "{%32,%33,%34,%35}, %36, 0, 1, 1, 0;"
    : "=r"(d[0]),"=r"(d[1]),"=r"(d[2]),"=r"(d[3]),"=r"(d[4]),"=r"(d[5]),"=r"(d[6]),"=r"(d[7]),"=r"(d[8]),"=r"(d[9]),"=r"(d[10]),"=r"(d[11]),"=r"(d[12]),"=r"(d[13]),"=r"(d[14]),"=r"(d[15]),"=r"(d[16]),"=r"(d[17]),"=r"(d[18]),"=r"(d[19]),"=r"(d[20]),"=r"(d[21]),"=r"(d[22]),"=r"(d[23]),"=r"(d[24]),"=r"(d[25]),"=r"(d[26]),"=r"(d[27]),"=r"(d[28]),"=r"(d[29]),"=r"(d[30]),"=r"(d[31])
    : "r"(a[0]), "r"(a[1]), "r"(a[2]), "r"(a[3]), "l"(desc));
}

__global__ void __launch_bounds__(256) k_mod(const bf16* __restrict__ c, const bf16* __restrict__ wm) {
  pdl_trigger();
  __shared__ float red[8][32];
  const int tid = threadIdx.x, r = tid >> 2, cc = tid & 3, lane = tid & 31, w = tid >> 5;
  uint4 v[8];
#pragma unroll
  for (int i = 0; i < 8; i++) v[i] = ldg128_nc(wm + (size_t)(r + 64 * i) * (6 * D_) + blockIdx.x * 32 + cc * 8);
  if (blockIdx.x < 8) g_flags[blockIdx.x * 256 + tid] = 0;
  float acc[8];
#pragma unroll
  for (int e = 0; e < 8; e++) acc[e] = 0.f;
#pragma unroll
  for (int i = 0; i < 8; i++) {
    float cv = __bfloat162float(c[r + 64 * i]);
    float s = __bfloat162float(__float2bfloat16(cv / (1.f + __expf(-cv))));
    uint32_t u[4] = {v[i].x, v[i].y, v[i].z, v[i].w};
#pragma unroll
    for (int e = 0; e < 4; e++) { acc[2 * e] += s * bf_lo(u[e]); acc[2 * e + 1] += s * bf_hi(u[e]); }
  }
#pragma unroll
  for (int e = 0; e < 8; e++) {
    acc[e] += __shfl_xor_sync(~0u, acc[e], 4);
    acc[e] += __shfl_xor_sync(~0u, acc[e], 8);
    acc[e] += __shfl_xor_sync(~0u, acc[e], 16);
  }
  if (lane < 4) {
#pragma unroll
    for (int e = 0; e < 8; e++) red[w][lane * 8 + e] = acc[e];
  }
  __syncthreads();
  if (tid < 32) {
    float s = 0.f;
#pragma unroll
    for (int i = 0; i < 8; i++) s += red[i][tid];
    const int col = blockIdx.x * 32 + tid, seg = col >> 9;
    bf16 m = __float2bfloat16(s);
    if (seg == 1 || seg == 4) m = __float2bfloat16(1.f + __bfloat162float(m));
    g_mod[col] = m;
  }
}

constexpr int QKV_SMEM = 24 * 8192 + 2048 + 256 + 1024;
__global__ void __launch_bounds__(256, 1) k_qkv(const __grid_constant__ CUtensorMap tm_w, const bf16* __restrict__ x) {
  extern __shared__ __align__(1024) uint8_t sp[];
  const uint32_t sb = smem_u32(sp), dlo = desc_lo(sb, 8192);
  const uint32_t bars = sb + 24 * 8192 + 2048;
  const int tid = threadIdx.x, lane = tid & 31, w = tid >> 5, g = lane >> 2, q = lane & 3;
  const int nt = blockIdx.x & 7, rb16 = (blockIdx.x >> 3) * 8 + w;
  pdl_trigger();
  if (tid == 0) {
    for (int i = 0; i < 6; i++) mbar_init(bars + 8 * i, 1);
    asm volatile("fence.mbarrier_init.release.cluster;" ::: "memory");
    for (int i = 0; i < 6; i++) {
      mbar_expect(bars + 8 * i, 4 * 8192);
      for (int kb = 0; kb < 4; kb++)
        tma5d(sb + (i * 4 + kb) * 8192, &tm_w, nt * 192 + (i >> 1) * 64, ((i & 1) * 4 + kb) * 2, bars + 8 * i);
    }
  }
  uint32_t a[128];
  {
    const bf16* x0 = x + (size_t)(rb16 * 16 + g) * D_ + q * 8;
#pragma unroll
    for (int b = 0; b < 16; b++) {
      uint4 u = ldg128_nc(x0 + b * 32), v = ldg128_nc(x0 + 8 * D_ + b * 32);
      a[8 * b] = u.x; a[8 * b + 2] = u.y; a[8 * b + 4] = u.z; a[8 * b + 6] = u.w;
      a[8 * b + 1] = v.x; a[8 * b + 3] = v.y; a[8 * b + 5] = v.z; a[8 * b + 7] = v.w;
    }
    float s[4] = {0.f, 0.f, 0.f, 0.f};
#pragma unroll
    for (int i = 0; i < 128; i++) { s[i & 1] += bf_lo(a[i]); s[2 + (i & 1)] += bf_hi(a[i]); }
    float m0 = s[0] + s[2], m1 = s[1] + s[3];
    m0 += __shfl_xor_sync(~0u, m0, 1); m1 += __shfl_xor_sync(~0u, m1, 1);
    m0 += __shfl_xor_sync(~0u, m0, 2); m1 += __shfl_xor_sync(~0u, m1, 2);
    m0 *= -1.f / D_; m1 *= -1.f / D_;
    const uint32_t one = 0x3F803F80u, nm0 = pack_bf16(m0, m0), nm1 = pack_bf16(m1, m1);
    s[0] = s[1] = s[2] = s[3] = 0.f;
#pragma unroll
    for (int i = 0; i < 128; i++) {
      a[i] = bf_fma2(a[i], one, (i & 1) ? nm1 : nm0);
      float lo = bf_lo(a[i]), hi = bf_hi(a[i]);
      s[i & 1] += lo * lo; s[2 + (i & 1)] += hi * hi;
    }
    float v0 = s[0] + s[2], v1 = s[1] + s[3];
    v0 += __shfl_xor_sync(~0u, v0, 1); v1 += __shfl_xor_sync(~0u, v1, 1);
    v0 += __shfl_xor_sync(~0u, v0, 2); v1 += __shfl_xor_sync(~0u, v1, 2);
    v0 = rsqrtf(v0 * (1.f / D_) + 1e-5f); v1 = rsqrtf(v1 * (1.f / D_) + 1e-5f);
    const uint32_t r0 = pack_bf16(v0, v0), r1 = pack_bf16(v1, v1);
#pragma unroll
    for (int i = 0; i < 128; i++) a[i] = bf_fma2(a[i], (i & 1) ? r1 : r0, 0x80008000u);
  }
  pdl_wait();
  if (tid < 128) *(uint4*)(sp + 24 * 8192 + tid * 16) = ldg128((const uint8_t*)g_mod + tid * 16);
  __syncthreads();
  float acc[2][32];
#pragma unroll
  for (int kb = 0; kb < 8; kb++) {
#pragma unroll
    for (int b = 2 * kb; b < 2 * kb + 2; b++) {
      uint4 sa = *(const uint4*)(sp + 24 * 8192 + b * 64 + q * 16), ca = *(const uint4*)(sp + 24 * 8192 + 1024 + b * 64 + q * 16);
      uint32_t su[4] = {sa.x, sa.y, sa.z, sa.w}, cu[4] = {ca.x, ca.y, ca.z, ca.w};
#pragma unroll
      for (int j = 0; j < 8; j++) a[8 * b + j] = bf_fma2(a[8 * b + j], cu[j >> 1], su[j >> 1]);
    }
    if ((kb & 3) == 0) mbar_wait(bars + 8 * (kb >> 2), 0);
    wg_fence();
#pragma unroll
    for (int ks = 0; ks < 4; ks++) MMA(mma_n64, kb * 8192 + ks * 2048, kb | ks, acc[0], a + (kb * 4 + ks) * 4, dlo);
  }
  wg_commit();
#pragma unroll
  for (int p = 0; p < 3; p++) {
    if (p < 2) {
      mbar_wait(bars + 8 * (2 * p + 2), 0);
      mbar_wait(bars + 8 * (2 * p + 3), 0);
      wg_fence();
#pragma unroll
      for (int ks = 0; ks < 32; ks++) MMA(mma_n64, (p + 1) * 65536 + ks * 2048, ks, acc[(p + 1) & 1], a + ks * 4, dlo);
      wg_commit();
      wg_wait<1>();
    } else {
      wg_wait<0>();
    }
    float* d = acc[p & 1];
    reg_fence<32>(d);
    const int col = nt * 192 + p * 64, sec = col >> 9, h0 = (col & 511) >> 4;
    if (sec == 0) {
      const float sc = 0.25f * 1.4426950408889634f;
#pragma unroll
      for (int hh = 0; hh < 4; hh++)
        g_q[((h0 + hh) * 128 + rb16) * 32 + lane] =
            make_uint4(pack_f16(d[8 * hh] * sc, d[8 * hh + 1] * sc), pack_f16(d[8 * hh + 2] * sc, d[8 * hh + 3] * sc),
                       pack_f16(d[8 * hh + 4] * sc, d[8 * hh + 5] * sc), pack_f16(d[8 * hh + 6] * sc, d[8 * hh + 7] * sc));
    } else {
      uint32_t* dst = (uint32_t*)(sec == 1 ? g_k : g_v) + (size_t)(h0 * 2 * S_ + rb16 * 16) * 4 + lane;
#pragma unroll
      for (int jj = 0; jj < 8; jj++) {
        dst[jj * S_ * 4] = pack_f16(d[4 * jj], d[4 * jj + 1]);
        dst[jj * S_ * 4 + 32] = pack_f16(d[4 * jj + 2], d[4 * jj + 3]);
      }
    }
  }
}

__device__ __forceinline__ uint32_t h_max(uint32_t a, uint32_t b) { uint32_t r; asm("max.f16x2 %0, %1, %2;" : "=r"(r) : "r"(a), "r"(b)); return r; }
__device__ __forceinline__ uint32_t h_add(uint32_t a, uint32_t b) { uint32_t r; asm("add.rn.f16x2 %0, %1, %2;" : "=r"(r) : "r"(a), "r"(b)); return r; }
__device__ __forceinline__ uint32_t h_sub(uint32_t a, uint32_t b) { uint32_t r; asm("sub.rn.f16x2 %0, %1, %2;" : "=r"(r) : "r"(a), "r"(b)); return r; }
__device__ __forceinline__ uint32_t h_mul(uint32_t a, uint32_t b) { uint32_t r; asm("mul.rn.f16x2 %0, %1, %2;" : "=r"(r) : "r"(a), "r"(b)); return r; }
__device__ __forceinline__ uint32_t h_fma(uint32_t a, uint32_t b, uint32_t c) { uint32_t r; asm("fma.rn.f16x2 %0, %1, %2, %3;" : "=r"(r) : "r"(a), "r"(b), "r"(c)); return r; }
__device__ __forceinline__ uint32_t h_fma_relu(uint32_t a, uint32_t b, uint32_t c) { uint32_t r; asm("fma.rn.relu.f16x2 %0, %1, %2, %3;" : "=r"(r) : "r"(a), "r"(b), "r"(c)); return r; }
__device__ __forceinline__ uint32_t h_ex2(uint32_t a) { uint32_t r; asm("ex2.approx.f16x2 %0, %1;" : "=r"(r) : "r"(a)); return r; }
__device__ __forceinline__ float h_lo(uint32_t v) { return __half2float(__ushort_as_half((unsigned short)(v & 0xffff))); }
__device__ __forceinline__ float h_hi(uint32_t v) { return __half2float(__ushort_as_half((unsigned short)(v >> 16))); }

__device__ __forceinline__ uint32_t exp2_fma(uint32_t s, uint32_t cp) {
  const uint32_t u = h_fma_relu(s, 0x18001800u, cp);
  const uint32_t n = h_mul(u, 0x02000200u);
  const uint32_t f = h_fma(n, 0xF800F800u, u);
  uint32_t p = h_fma(f, 0x630D630Du, 0x47C047C0u);
  p = h_fma(p, f, 0x298C298Cu);
  p = h_fma(p, f, 0x08000800u);
  return p + (n << 10);
}

#define NPOLY 8
__device__ __forceinline__ constexpr bool is_poly(int i) { return ((i & 15) * NPOLY) / 16 != (((i & 15) + 1) * NPOLY) / 16; }

constexpr int ATT_SMEM = 5 * 32768 + 128 + 1024;
__global__ void __launch_bounds__(512, 1) k_attn(const bf16* __restrict__ wo, const bf16* __restrict__ w1,
                                                 const bf16* __restrict__ w3, const bf16* __restrict__ w2) {
  extern __shared__ __align__(1024) uint8_t sp[];
  const uint32_t sb = smem_u32(sp);
  const uint32_t bars = sb + 5 * 32768;
  const int tid = threadIdx.x, lane = tid & 31, w = tid >> 5;
  const int head = blockIdx.x >> 2, quarter = blockIdx.x & 3;
  if (tid == 0) {
    for (int i = 0; i < 8; i++) mbar_init(bars + 8 * i, 1);
    asm volatile("fence.mbarrier_init.release.cluster;" ::: "memory");
  }
#pragma unroll
  for (int i = 0; i < 4; i++) *(uint4*)(sp + 4 * 32768 + (i * 512 + tid) * 16) = make_uint4(0x3C003C00u, 0x3C003C00u, 0x3C003C00u, 0x3C003C00u);
  asm volatile("fence.proxy.async.shared::cta;" ::: "memory");
  __syncthreads();
  pdl_wait();
  if (tid == 0) {
    for (int i = 0; i < 8; i++) {
      mbar_expect(bars + 8 * i, 16384);
      bulk_g2s(sb + i * 4096, g_k + (head * 2) * S_ + i * 256, 4096, bars + 8 * i);
      bulk_g2s(sb + 32768 + i * 4096, g_k + (head * 2 + 1) * S_ + i * 256, 4096, bars + 8 * i);
      bulk_g2s(sb + 65536 + i * 4096, g_v + (head * 2) * S_ + i * 256, 4096, bars + 8 * i);
      bulk_g2s(sb + 98304 + i * 4096, g_v + (head * 2 + 1) * S_ + i * 256, 4096, bars + 8 * i);
    }
  }
  pdl_trigger();
  if (tid == 64) {
    l2_prefetch((const uint8_t*)wo + blockIdx.x * 4096, 4096);
    l2_prefetch((const uint8_t*)w1 + blockIdx.x * 11008, 11008);
    l2_prefetch((const uint8_t*)w3 + blockIdx.x * 11008, 11008);
    l2_prefetch((const uint8_t*)w2 + blockIdx.x * 11008, 11008);
  }
  const uint64_t dk0 = desc_plain(sb, 32768, 128);
  const uint32_t dv0 = desc_lo(sb + 65536, 128);
#pragma unroll 1
  for (int t = 0; t < 2; t++) {
    const int rb16 = quarter * 32 + (w >> 2) * 8 + t * 4 + (w & 3);
    uint32_t qf[4];
    { uint4 u = ldg128(g_q + (head * 128 + rb16) * 32 + lane); qf[0] = u.x; qf[1] = u.y; qf[2] = u.z; qf[3] = u.w; }
    float o[12];
#pragma unroll
    for (int i = 0; i < 12; i++) o[i] = 0.f;
    uint32_t M = 0xFBFFFBFFu, cprev = 0x7BFF7BFFu;
    uint32_t s[64];
#pragma unroll 1
    for (int kb = 0; kb < 8; kb++) {
      if (t == 0) mbar_wait(bars + 8 * kb, 0);
      wg_fence();
      mma_qk256(s, qf, dk0 + kb * 256);
      wg_commit();
      wg_wait<0>();
      reg_fence<64>(s);
      uint32_t m0 = h_max(s[0], s[2]), m1 = h_max(s[1], s[3]), m2 = h_max(s[4], s[6]), m3 = h_max(s[5], s[7]);
#pragma unroll
      for (int i = 8; i < 64; i += 8) {
        m0 = h_max(h_max(m0, s[i]), s[i + 2]); m1 = h_max(h_max(m1, s[i + 1]), s[i + 3]);
        m2 = h_max(h_max(m2, s[i + 4]), s[i + 6]); m3 = h_max(h_max(m3, s[i + 5]), s[i + 7]);
      }
      m0 = h_max(m0, m2); m1 = h_max(m1, m3);
      M = h_max(h_max(__byte_perm(m0, m1, 0x5410), __byte_perm(m0, m1, 0x7632)), M);
      M = h_max(M, __shfl_xor_sync(~0u, M, 1));
      M = h_max(M, __shfl_xor_sync(~0u, M, 2));
      const uint32_t c = h_sub(h_sub(0x660E660Eu, M), 0x66006600u);
      const uint32_t cp = h_fma(c, 0x18001800u, 0x26802680u);
      const uint32_t dl = h_sub(c, cprev);
      cprev = c;
      const float a0 = ex2f(h_lo(dl)), a1 = ex2f(h_hi(dl));
      const uint32_t c0 = __byte_perm(c, c, 0x1010), c1 = __byte_perm(c, c, 0x3232);
      const uint32_t p0 = __byte_perm(cp, cp, 0x1010), p1 = __byte_perm(cp, cp, 0x3232);
      o[0] *= a0; o[1] *= a0; o[4] *= a0; o[5] *= a0; o[8] *= a0;
      o[2] *= a1; o[3] *= a1; o[6] *= a1; o[7] *= a1; o[10] *= a1;
#pragma unroll
      for (int grp = 0; grp < 4; grp++) {
#pragma unroll
        for (int i = grp * 16; i < grp * 16 + 16; i++)
          s[i] = is_poly(i) ? exp2_fma(s[i], (i & 1) ? p1 : p0) : h_ex2(h_add(s[i], (i & 1) ? c1 : c0));
        wg_fence();
#pragma unroll
        for (int ks = grp * 4; ks < grp * 4 + 4; ks++) mma_pv24(o, s + ks * 4, dv0 + kb * 256, ks * 256, 1);
      }
      wg_commit();
      wg_wait<0>();
      reg_fence<12>(o);
    }
    const float i0 = 1.f / o[8], i1 = 1.f / o[10];
    g_attn[(rb16 * 32 + head) * 32 + lane] = make_uint4(pack_bf16(o[0] * i0, o[1] * i0), pack_bf16(o[2] * i1, o[3] * i1),
                                                        pack_bf16(o[4] * i0, o[5] * i0), pack_bf16(o[6] * i1, o[7] * i1));
  }
}

__device__ float4 g_stats[128 * 16 * 4];
constexpr int NST = 13, STB = 16384;
constexpr int FFN_SMEM = NST * STB + 4096 + 512 + 1024;

__device__ __forceinline__ void flag_signal(unsigned* f, int lane) {
  __syncwarp();
  if (lane == 0) asm volatile("red.release.gpu.global.add.u32 [%0], 1;" ::"l"(f) : "memory");
}
__device__ __forceinline__ void flag_wait(const unsigned* f, int lane) {
  if (lane == 0) {
    unsigned v, n = 0;
    do {
      asm volatile("ld.acquire.gpu.global.u32 %0, [%1];" : "=r"(v) : "l"(f) : "memory");
      if (++n > (1u << 24)) __trap();
    } while (v < 8);
  }
  __syncwarp();
}
__device__ __forceinline__ float silu_mul(float g, float u) { return g * u * rcpf(1.f + ex2f(g * -1.4426950408889634f)); }

__global__ void __launch_bounds__(384, 1) __cluster_dims__(2, 1, 1)
k_ffn(const __grid_constant__ CUtensorMap tm_wo, const __grid_constant__ CUtensorMap tm_w1, const __grid_constant__ CUtensorMap tm_w3,
      const __grid_constant__ CUtensorMap tm_w2, const bf16* __restrict__ x, bf16* __restrict__ out) {
  extern __shared__ __align__(1024) uint8_t sp[];
  const uint32_t sb = smem_u32(sp), dlo = desc_lo(sb, 8192);
  const uint32_t bfull = sb + NST * STB + 4096, bempty = bfull + 8 * NST, bpeer = bempty + 8 * NST, bx = bpeer + 8;
  const int tid = threadIdx.x, lane = tid & 31, w = tid >> 5;
  const int j = blockIdx.x & 7, rb = blockIdx.x >> 3, kh = j & 1;
  if (tid == 0) {
    for (int i = 0; i < NST; i++) { mbar_init(bfull + 8 * i, 1); mbar_init(bempty + 8 * i, 8); }
    mbar_init(bpeer, 8);
    for (int i = 0; i < 8; i++) { mbar_init(bx + 8 * i, 1); }
    asm volatile("fence.mbarrier_init.release.cluster;" ::: "memory");
    for (int i = 0; i < 8; i++) mbar_expect(bx + 8 * i, 4096);
  }
  if (tid < 256) *(uint4*)(sp + NST * STB + tid * 16) = ldg128((const uint8_t*)g_mod + 2048 + tid * 16);
  __syncthreads();
  asm volatile("barrier.cluster.arrive.release.aligned;" ::: "memory");
  if (w >= 8) {
    asm volatile("setmaxnreg.dec.sync.aligned.u32 24;");
    if (tid == 256) {
      int slot = 0, ph = 1;
#pragma unroll 1
      for (int st = 0; st < 39; st++) {
        const CUtensorMap *m0, *m1; int x0, y0, x1, y1;
        if (st < 4) { m0 = m1 = &tm_wo; x0 = x1 = j * 64; y0 = st * 128; y1 = y0 + 64; }
        else if (st < 28) { m0 = &tm_w1; m1 = &tm_w3; x0 = x1 = j * 176 + ((st - 4) >> 3) * 64; y0 = y1 = ((st - 4) & 7) * 64; }
        else { m0 = m1 = &tm_w2; x0 = (j >> 1) * 128; x1 = x0 + 64; y0 = y1 = kh * 688 + (st - 28) * 64; }
        mbar_wait(bempty + 8 * slot, ph);
        mbar_expect(bfull + 8 * slot, STB);
        tma2d(sb + slot * STB, m0, x0, y0, bfull + 8 * slot);
        tma2d(sb + slot * STB + 8192, m1, x1, y1, bfull + 8 * slot);
        if (++slot == NST) { slot = 0; ph ^= 1; }
      }
    }
    __syncwarp();
    asm volatile("barrier.cluster.wait.acquire.aligned;" ::: "memory");
  } else {
    asm volatile("setmaxnreg.inc.sync.aligned.u32 240;");
    const int g = lane >> 2, q = lane & 3, rb16 = rb * 8 + w;
    const uint32_t* smod = (const uint32_t*)(sp + NST * STB);
    uint32_t a[128];
    float acc[64];
    uint32_t xr[16];
    {
      const uint32_t* x0 = (const uint32_t*)(x + (size_t)(rb16 * 16 + g) * D_ + j * 64) + q;
#pragma unroll
      for (int i = 0; i < 8; i++) { xr[2 * i] = __ldg(x0 + i * 4); xr[2 * i + 1] = __ldg(x0 + 8 * D_ / 2 + i * 4); }
    }
    asm volatile("barrier.cluster.wait.acquire.aligned;" ::: "memory");
    pdl_wait();
#pragma unroll
    for (int i = 0; i < 32; i++) { uint4 u = ldg128(g_attn + (rb16 * 32 + i) * 32 + lane); a[4 * i] = u.x; a[4 * i + 1] = u.y; a[4 * i + 2] = u.z; a[4 * i + 3] = u.w; }
#pragma unroll
    for (int st = 0; st < 4; st++) {
      mbar_wait(bfull + 8 * st, 0);
      wg_fence();
#pragma unroll
      for (int ks = 0; ks < 8; ks++) MMA(mma_n64, st * STB + ks * 2048, st | ks, acc, a + (st * 8 + ks) * 4, dlo);
    }
    wg_commit();
    wg_wait<0>();
    reg_fence<32>(acc);
    if (lane < 4) mbar_arrive(bempty + 8 * lane);
    {
      float s0 = 0.f, s1 = 0.f;
#pragma unroll
      for (int i = 0; i < 8; i++) {
        const uint32_t ga = smod[j * 32 + i * 4 + q];
        xr[2 * i] = pack_bf16(bf_lo(xr[2 * i]) + bf_lo(ga) * acc[4 * i], bf_hi(xr[2 * i]) + bf_hi(ga) * acc[4 * i + 1]);
        xr[2 * i + 1] = pack_bf16(bf_lo(xr[2 * i + 1]) + bf_lo(ga) * acc[4 * i + 2], bf_hi(xr[2 * i + 1]) + bf_hi(ga) * acc[4 * i + 3]);
        s0 += bf_lo(xr[2 * i]) + bf_hi(xr[2 * i]); s1 += bf_lo(xr[2 * i + 1]) + bf_hi(xr[2 * i + 1]);
      }
#pragma unroll
      for (int i = 0; i < 4; i++) g_x1[(rb16 * 32 + j * 4 + i) * 32 + lane] = make_uint4(xr[4 * i], xr[4 * i + 1], xr[4 * i + 2], xr[4 * i + 3]);
      s0 += __shfl_xor_sync(~0u, s0, 1); s1 += __shfl_xor_sync(~0u, s1, 1);
      s0 += __shfl_xor_sync(~0u, s0, 2); s1 += __shfl_xor_sync(~0u, s1, 2);
      s0 *= 1.f / 64; s1 *= 1.f / 64;
      float v0 = 0.f, v1 = 0.f;
#pragma unroll
      for (int i = 0; i < 8; i++) {
        float d = bf_lo(xr[2 * i]) - s0; v0 += d * d; d = bf_hi(xr[2 * i]) - s0; v0 += d * d;
        d = bf_lo(xr[2 * i + 1]) - s1; v1 += d * d; d = bf_hi(xr[2 * i + 1]) - s1; v1 += d * d;
      }
      v0 += __shfl_xor_sync(~0u, v0, 1); v1 += __shfl_xor_sync(~0u, v1, 1);
      v0 += __shfl_xor_sync(~0u, v0, 2); v1 += __shfl_xor_sync(~0u, v1, 2);
      if (q < 2) ((float2*)g_stats)[(rb16 * 16 + g + q * 8) * 8 + j] = q ? make_float2(s1, v1) : make_float2(s0, v0);
    }
    flag_signal(g_flags + rb16 * 8, lane);
    flag_wait(g_flags + rb16 * 8, lane);
    uint32_t r0, r1, n0, n1;
    {
      uint4 t0 = ldg128(g_stats + (rb16 * 16 + g) * 4 + q), t1 = ldg128(g_stats + (rb16 * 16 + g + 8) * 4 + q);
#pragma unroll
      for (int i = 0; i < 32; i++) { uint4 u = ldg128(g_x1 + (rb16 * 32 + i) * 32 + lane); a[4 * i] = u.x; a[4 * i + 1] = u.y; a[4 * i + 2] = u.z; a[4 * i + 3] = u.w; }
      float m0 = __uint_as_float(t0.x) + __uint_as_float(t0.z), m1 = __uint_as_float(t1.x) + __uint_as_float(t1.z);
      m0 += __shfl_xor_sync(~0u, m0, 1); m1 += __shfl_xor_sync(~0u, m1, 1);
      m0 += __shfl_xor_sync(~0u, m0, 2); m1 += __shfl_xor_sync(~0u, m1, 2);
      m0 *= 0.125f; m1 *= 0.125f;
      float d0 = __uint_as_float(t0.x) - m0, d1 = __uint_as_float(t0.z) - m0;
      float v0 = __uint_as_float(t0.y) + __uint_as_float(t0.w) + 64.f * (d0 * d0 + d1 * d1);
      d0 = __uint_as_float(t1.x) - m1; d1 = __uint_as_float(t1.z) - m1;
      float v1 = __uint_as_float(t1.y) + __uint_as_float(t1.w) + 64.f * (d0 * d0 + d1 * d1);
      v0 += __shfl_xor_sync(~0u, v0, 1); v1 += __shfl_xor_sync(~0u, v1, 1);
      v0 += __shfl_xor_sync(~0u, v0, 2); v1 += __shfl_xor_sync(~0u, v1, 2);
      v0 = rsqrtf(v0 * (1.f / D_) + 1e-5f); v1 = rsqrtf(v1 * (1.f / D_) + 1e-5f);
      r0 = pack_bf16(v0, v0); r1 = pack_bf16(v1, v1);
      m0 *= -bf_lo(r0); m1 *= -bf_lo(r1);
      n0 = pack_bf16(m0, m0); n1 = pack_bf16(m1, m1);
    }
#pragma unroll
    for (int p = 0; p < 3; p++) {
      float g48[24], u48[24];
#pragma unroll
      for (int kb = 0; kb < 8; kb++) {
        const int st = 4 + p * 8 + kb, slot = st % NST;
        if (p == 0) {
#pragma unroll
          for (int i = kb * 8; i < kb * 8 + 8; i++) {
            const uint32_t sv = smod[256 + i * 4 + q], cv = smod[512 + i * 4 + q];
            a[2 * i] = bf_fma2(bf_fma2(a[2 * i], r0, n0), cv, sv);
            a[2 * i + 1] = bf_fma2(bf_fma2(a[2 * i + 1], r1, n1), cv, sv);
          }
        }
        mbar_wait(bfull + 8 * slot, (st / NST) & 1);
        wg_fence();
#pragma unroll
        for (int ks = 0; ks < 4; ks++) {
          if (p < 2) MMA(mma_n128, slot * STB + ks * 2048, kb | ks, acc, a + (kb * 4 + ks) * 4, dlo);
          else {
            MMA(mma_n48, slot * STB + ks * 2048, kb | ks, g48, a + (kb * 4 + ks) * 4, dlo);
            MMA(mma_n48, slot * STB + 8192 + ks * 2048, kb | ks, u48, a + (kb * 4 + ks) * 4, dlo);
          }
        }
        wg_commit();
        if (kb > 0) { wg_wait<1>(); if (lane == 0) mbar_arrive(bempty + 8 * ((st - 1) % NST)); }
      }
      wg_wait<0>();
      if (p < 2) reg_fence<64>(acc); else { reg_fence<24>(g48); reg_fence<24>(u48); }
      if (lane == 0) {
        mbar_arrive(bempty + 8 * ((4 + p * 8 + 7) % NST));
        if (p == 2) {
          uint32_t ra; asm volatile("mapa.shared::cluster.u32 %0, %1, %2;" : "=r"(ra) : "r"(bpeer), "r"(kh ^ 1));
          asm volatile("mbarrier.arrive.shared::cluster.b64 _, [%0];" ::"r"(ra) : "memory");
        }
      }
#pragma unroll
      for (int ks = 0; ks < (p < 2 ? 4 : 3); ks++) {
        const int kk = j * 11 + p * 4 + ks;
        const float* gt = (p < 2 ? acc : g48) + 8 * ks; const float* up = (p < 2 ? acc + 32 : u48) + 8 * ks;
        uint4 u = make_uint4(pack_bf16(silu_mul(gt[0], up[0]), silu_mul(gt[1], up[1])), pack_bf16(silu_mul(gt[2], up[2]), silu_mul(gt[3], up[3])),
                             pack_bf16(silu_mul(gt[4], up[4]), silu_mul(gt[5], up[5])), pack_bf16(silu_mul(gt[6], up[6]), silu_mul(gt[7], up[7])));
        if (kk < KS_F) g_act[(rb16 * KS_F + kk) * 32 + lane] = u;
      }
    }
    flag_signal(g_flags + 1024 + rb16 * 8, lane);
    flag_wait(g_flags + 1024 + rb16 * 8, lane);
    float acc3[64];
    const uint4* ap = g_act + (rb16 * KS_F + kh * 43) * 32 + lane;
#pragma unroll
    for (int i = 0; i < 32; i++) { uint4 u = ldg128(ap + i * 32); a[4 * i] = u.x; a[4 * i + 1] = u.y; a[4 * i + 2] = u.z; a[4 * i + 3] = u.w; }
#pragma unroll
    for (int kb = 0; kb < 11; kb++) {
      const int slot = (28 + kb) % NST;
      mbar_wait(bfull + 8 * slot, 0);
      wg_fence();
#pragma unroll
      for (int ks = 0; ks < (kb < 10 ? 4 : 3); ks++)
        MMA(mma_n128, slot * STB + ks * 2048, kb | ks, acc3, a + ((kb * 4 + ks) & 31) * 4, dlo);
      wg_commit();
      if (kb == 2) {
        wg_wait<0>();
        reg_fence<64>(acc3);
#pragma unroll
        for (int i = 0; i < 11; i++) { uint4 u = ldg128(ap + (32 + i) * 32); a[4 * i] = u.x; a[4 * i + 1] = u.y; a[4 * i + 2] = u.z; a[4 * i + 3] = u.w; }
      }
    }
#pragma unroll
    for (int i = 0; i < 4; i++) { uint4 u = ldg128(g_x1 + (rb16 * 32 + j * 4 + i) * 32 + lane); xr[4 * i] = u.x; xr[4 * i + 1] = u.y; xr[4 * i + 2] = u.z; xr[4 * i + 3] = u.w; }
    mbar_wait_cluster(bpeer, 0);
    wg_wait<0>();
    reg_fence<64>(acc3);
    {
      uint32_t ra, rbar;
      asm volatile("mapa.shared::cluster.u32 %0, %1, %2;" : "=r"(ra) : "r"(sb + tid * 16), "r"(kh ^ 1));
      asm volatile("mapa.shared::cluster.u32 %0, %1, %2;" : "=r"(rbar) : "r"(bx + 8 * w), "r"(kh ^ 1));
#pragma unroll
      for (int i = 0; i < 8; i++) {
        const float s0 = kh ? acc3[4 * i] : acc3[32 + 4 * i], s1 = kh ? acc3[4 * i + 1] : acc3[33 + 4 * i];
        const float s2 = kh ? acc3[4 * i + 2] : acc3[34 + 4 * i], s3 = kh ? acc3[4 * i + 3] : acc3[35 + 4 * i];
        asm volatile("st.async.weak.shared::cluster.mbarrier::complete_tx::bytes.v4.f32 [%0], {%1,%2,%3,%4}, [%5];"
                     ::"r"(ra + i * 4096), "f"(s0), "f"(s1), "f"(s2), "f"(s3), "r"(rbar) : "memory");
      }
    }
    mbar_wait_cluster(bx + 8 * w, 0);
    uint32_t* o0 = (uint32_t*)(out + (size_t)(rb16 * 16 + g) * D_ + j * 64) + q;
#pragma unroll
    for (int i = 0; i < 8; i++) {
      const float4 pv = *(const float4*)(sp + i * 4096 + tid * 16);
      const uint32_t gb = smod[768 + j * 32 + i * 4 + q];
      const float s0 = (kh ? acc3[32 + 4 * i] : acc3[4 * i]) + pv.x, s1 = (kh ? acc3[33 + 4 * i] : acc3[4 * i + 1]) + pv.y;
      const float s2 = (kh ? acc3[34 + 4 * i] : acc3[4 * i + 2]) + pv.z, s3 = (kh ? acc3[35 + 4 * i] : acc3[4 * i + 3]) + pv.w;
      o0[i * 4] = pack_bf16(bf_lo(xr[2 * i]) + bf_lo(gb) * s0, bf_hi(xr[2 * i]) + bf_hi(gb) * s1);
      o0[8 * D_ / 2 + i * 4] = pack_bf16(bf_lo(xr[2 * i + 1]) + bf_lo(gb) * s2, bf_hi(xr[2 * i + 1]) + bf_hi(gb) * s3);
    }
  }
}

typedef CUresult (*EncodeFn)(CUtensorMap*, CUtensorMapDataType, cuuint32_t, void*, const cuuint64_t*, const cuuint64_t*,
                             const cuuint32_t*, const cuuint32_t*, CUtensorMapInterleave, CUtensorMapSwizzle,
                             CUtensorMapL2promotion, CUtensorMapFloatOOBfill);
static void make_map(EncodeFn enc, CUtensorMap* m, const void* p, int rank, const cuuint64_t* dims, const cuuint64_t* strides, const cuuint32_t* box) {
  const cuuint32_t es[5] = {1, 1, 1, 1, 1};
  enc(m, CU_TENSOR_MAP_DATA_TYPE_BFLOAT16, rank, (void*)p, dims, strides, box, es, CU_TENSOR_MAP_INTERLEAVE_NONE,
      CU_TENSOR_MAP_SWIZZLE_128B, CU_TENSOR_MAP_L2_PROMOTION_L2_256B, CU_TENSOR_MAP_FLOAT_OOB_FILL_NONE);
}
static void make_map2(EncodeFn enc, CUtensorMap* m, const void* p, int cols, int rows) {
  const cuuint64_t dims[2] = {(cuuint64_t)cols, (cuuint64_t)rows}, st[1] = {(cuuint64_t)cols * 2};
  const cuuint32_t box[2] = {64, 64};
  make_map(enc, m, p, 2, dims, st, box);
}
template <typename... KA, typename... A>
static void launch(void (*k)(KA...), int grid, int block, int smem, bool pdl, A... args) {
  cudaLaunchConfig_t cfg = {};
  cfg.gridDim = dim3(grid); cfg.blockDim = dim3(block); cfg.dynamicSmemBytes = smem; cfg.stream = cudaStreamPerThread;
  cudaLaunchAttribute at[1];
  at[0].id = cudaLaunchAttributeProgrammaticStreamSerialization;
  at[0].val.programmaticStreamSerializationAllowed = 1;
  cfg.attrs = at; cfg.numAttrs = pdl ? 1 : 0;
  cudaLaunchKernelEx(&cfg, k, KA(args)...);
}

extern "C" void kernel_launch(void* const* d_in, const int* in_sizes, int n_in, void* d_out, int out_size) {
  const bf16 *x = (const bf16*)d_in[0], *wqkv = (const bf16*)d_in[1], *wo = (const bf16*)d_in[2];
  const bf16 *w1 = (const bf16*)d_in[4], *w3 = (const bf16*)d_in[5], *w2 = (const bf16*)d_in[6];
  const bf16 *c = (const bf16*)d_in[7], *wm = (const bf16*)d_in[8];
  void* fn = nullptr;
  cudaDriverEntryPointQueryResult qr;
  cudaGetDriverEntryPoint("cuTensorMapEncodeTiled", &fn, cudaEnableDefault, &qr);
  EncodeFn enc = (EncodeFn)fn;
  CUtensorMap m_qkv, m_o, m_1, m_3, m_2;
  {
    const cuuint64_t rs = 3 * D_ * 2, dims[5] = {3 * D_, 2, 4, 4, 16}, st[4] = {rs, 8 * rs, 2 * rs, 32 * rs};
    const cuuint32_t box[5] = {64, 2, 4, 4, 2};
    make_map(enc, &m_qkv, wqkv, 5, dims, st, box);
  }
  make_map2(enc, &m_o, wo, D_, D_);
  make_map2(enc, &m_1, w1, F_, D_);
  make_map2(enc, &m_3, w3, F_, D_);
  make_map2(enc, &m_2, w2, D_, F_);
  cudaFuncSetAttribute(k_qkv, cudaFuncAttributeMaxDynamicSharedMemorySize, QKV_SMEM);
  cudaFuncSetAttribute(k_attn, cudaFuncAttributeMaxDynamicSharedMemorySize, ATT_SMEM);
  cudaFuncSetAttribute(k_ffn, cudaFuncAttributeMaxDynamicSharedMemorySize, FFN_SMEM);
  launch(k_mod, 96, 256, 0, false, c, wm);
  launch(k_qkv, 128, 256, QKV_SMEM, true, m_qkv, x);
  launch(k_attn, 128, 512, ATT_SMEM, true, wo, w1, w3, w2);
  launch(k_ffn, 128, 384, FFN_SMEM, true, m_o, m_1, m_3, m_2, x, (bf16*)d_out);
}
```

```cpp
#include <cuda_runtime.h>
#include <cuda_bf16.h>
#include <cuda_fp16.h>
#include <cuda.h>
#include <stdint.h>

typedef __nv_bfloat16 bf16;
constexpr int S_ = 2048, D_ = 512, F_ = 1376, NH = 32;
constexpr int KS_F = F_ / 16;

__device__ __align__(16) bf16 g_mod[6 * D_];
__device__ uint4 g_q[NH * 128 * 32];
__device__ uint4 g_k[NH * 2 * S_];
__device__ uint4 g_v[NH * 2 * S_];
__device__ uint4 g_attn[128 * 32 * 32];
__device__ uint4 g_x1[128 * 32 * 32];
__device__ uint4 g_act[128 * KS_F * 32];
__device__ unsigned g_flags[2 * 128 * 8];

__device__ __forceinline__ uint32_t smem_u32(const void* p) { return (uint32_t)__cvta_generic_to_shared(p); }
__device__ __forceinline__ void mbar_init(uint32_t b, uint32_t n) { asm volatile("mbarrier.init.shared::cta.b64 [%0], %1;" ::"r"(b), "r"(n) : "memory"); }
__device__ __forceinline__ void mbar_expect(uint32_t b, uint32_t bytes) { asm volatile("mbarrier.arrive.expect_tx.shared::cta.b64 _, [%0], %1;" ::"r"(b), "r"(bytes) : "memory"); }
__device__ __forceinline__ void mbar_arrive(uint32_t b) { asm volatile("mbarrier.arrive.shared::cta.b64 _, [%0];" ::"r"(b) : "memory"); }
__device__ __forceinline__ void mbar_wait(uint32_t b, uint32_t ph) {
  asm volatile("{.reg .pred p; .reg .u32 n; mov.u32 n, 0;\n"
               "W: mbarrier.try_wait.parity.shared::cta.b64 p, [%0], %1;\n"
               "@p bra D; add.u32 n, n, 1; setp.lt.u32 p, n, 0x4000000; @p bra W;\n"
               "D: }" ::"r"(b), "r"(ph) : "memory");
}
__device__ __forceinline__ void mbar_wait_cluster(uint32_t b, uint32_t ph) {
  asm volatile("{.reg .pred p; .reg .u32 n; mov.u32 n, 0;\n"
               "W: mbarrier.try_wait.parity.acquire.cluster.shared::cta.b64 p, [%0], %1;\n"
               "@p bra D; add.u32 n, n, 1; setp.lt.u32 p, n, 0x4000000; @p bra W;\n"
               "D: }" ::"r"(b), "r"(ph) : "memory");
}
__device__ __forceinline__ void tma2d(uint32_t dst, const CUtensorMap* m, int c0, int c1, uint32_t bar) {
  asm volatile("cp.async.bulk.tensor.2d.shared::cluster.global.mbarrier::complete_tx::bytes [%0], [%1, {%3, %4}], [%2];"
               ::"r"(dst), "l"(m), "r"(bar), "r"(c0), "r"(c1) : "memory");
}
__device__ __forceinline__ void tma5d(uint32_t dst, const CUtensorMap* m, int c0, int c4, uint32_t bar) {
  asm volatile("cp.async.bulk.tensor.5d.shared::cluster.global.mbarrier::complete_tx::bytes [%0], [%1, {%3, 0, 0, 0, %4}], [%2];"
               ::"r"(dst), "l"(m), "r"(bar), "r"(c0), "r"(c4) : "memory");
}
__device__ __forceinline__ void bulk_g2s(uint32_t dst, const void* src, uint32_t bytes, uint32_t bar) {
  asm volatile("cp.async.bulk.shared::cluster.global.mbarrier::complete_tx::bytes [%0], [%1], %2, [%3];"
               ::"r"(dst), "l"(src), "r"(bytes), "r"(bar) : "memory");
}
__device__ __forceinline__ void l2_prefetch(const void* src, uint32_t bytes) {
  asm volatile("cp.async.bulk.prefetch.L2.global [%0], %1;" ::"l"(src), "r"(bytes) : "memory");
}
__device__ __forceinline__ void pdl_wait() { asm volatile("griddepcontrol.wait;" ::: "memory"); }
__device__ __forceinline__ void pdl_trigger() { asm volatile("griddepcontrol.launch_dependents;" ::: "memory"); }
__device__ __forceinline__ void wg_fence() { asm volatile("wgmma.fence.sync.aligned;" ::: "memory"); }
__device__ __forceinline__ void wg_commit() { asm volatile("wgmma.commit_group.sync.aligned;" ::: "memory"); }
template <int N> __device__ __forceinline__ void wg_wait() { asm volatile("wgmma.wait_group.sync.aligned %0;" ::"n"(N) : "memory"); }
template <int N> __device__ __forceinline__ void reg_fence(float* r) {
#pragma unroll
  for (int i = 0; i < N; i++) asm volatile("" : "+f"(r[i])::"memory");
}
template <int N> __device__ __forceinline__ void reg_fence(uint32_t* r) {
#pragma unroll
  for (int i = 0; i < N; i++) asm volatile("" : "+r"(r[i])::"memory");
}
__device__ __forceinline__ uint4 ldg128(const void* p) {
  uint4 v; asm volatile("ld.global.L1::no_allocate.v4.u32 {%0,%1,%2,%3}, [%4];" : "=r"(v.x), "=r"(v.y), "=r"(v.z), "=r"(v.w) : "l"(p) : "memory"); return v;
}
__device__ __forceinline__ uint4 ldg128_nc(const void* p) {
  uint4 v; asm volatile("ld.global.nc.L1::no_allocate.v4.u32 {%0,%1,%2,%3}, [%4];" : "=r"(v.x), "=r"(v.y), "=r"(v.z), "=r"(v.w) : "l"(p)); return v;
}
__device__ __forceinline__ uint32_t pack_bf16(float lo, float hi) { uint32_t r; asm("cvt.rn.bf16x2.f32 %0, %1, %2;" : "=r"(r) : "f"(hi), "f"(lo)); return r; }
__device__ __forceinline__ uint32_t pack_f16(float lo, float hi) { uint32_t r; asm("cvt.rn.satfinite.f16x2.f32 %0, %1, %2;" : "=r"(r) : "f"(hi), "f"(lo)); return r; }
__device__ __forceinline__ float bf_lo(uint32_t v) { return __uint_as_float(v << 16); }
__device__ __forceinline__ float bf_hi(uint32_t v) { return __uint_as_float(v & 0xffff0000u); }
__device__ __forceinline__ uint32_t bf_fma2(uint32_t a, uint32_t b, uint32_t c) { uint32_t r; asm("fma.rn.bf16x2 %0, %1, %2, %3;" : "=r"(r) : "r"(a), "r"(b), "r"(c)); return r; }
__device__ __forceinline__ float ex2f(float x) { float r; asm("ex2.approx.ftz.f32 %0, %1;" : "=f"(r) : "f"(x)); return r; }
__device__ __forceinline__ float rcpf(float x) { float r; asm("rcp.approx.ftz.f32 %0, %1;" : "=f"(r) : "f"(x)); return r; }
__device__ __forceinline__ uint32_t desc_lo(uint32_t addr, uint32_t lbo) { return ((addr & 0x3FFFF) >> 4) | ((lbo >> 4) << 16); }
#define MMA(fn, off, accum, d, a, dlo) fn(d, a, dlo, off, accum)
__device__ __forceinline__ uint64_t desc_plain(uint32_t addr, uint32_t lbo, uint32_t sbo) {
  return (uint64_t)((addr & 0x3FFFF) >> 4) | ((uint64_t)(lbo >> 4) << 16) | ((uint64_t)(sbo >> 4) << 32);
}
#define NPOLY 9
__host__ __device__ constexpr bool poly_grp(int j) { return ((j & 15) * NPOLY) / 16 != (((j & 15) + 1) * NPOLY) / 16; }
#define TS(k, s, cond)
__device__ __forceinline__ void mma_qkc256(uint32_t* d, uint32_t c0, uint32_t c1, uint64_t dc, const uint32_t* a, uint64_t desc) {
  asm volatile("wgmma.mma_async.sync.aligned.m64n256k16.f16.f16.f16 {%0,%1,%2,%3,%4,%5,%6,%7,%8,%9,%10,%11,%12,%13,%14,%15,%16,%17,%18,%19,%20,%21,%22,%23,%24,%25,%26,%27,%28,%29,%30,%31,%32,%33,%34,%35,%36,%37,%38,%39,%40,%41,%42,%43,%44,%45,%46,%47,%48,%49,%50,%51,%52,%53,%54,%55,%56,%57,%58,%59,%60,%61,%62,%63}, "
    "{%69,%70,%71,%71}, %72, 0, 1, 1, 0;\n"
    "wgmma.mma_async.sync.aligned.m64n256k16.f16.f16.f16 {%0,%1,%2,%3,%4,%5,%6,%7,%8,%9,%10,%11,%12,%13,%14,%15,%16,%17,%18,%19,%20,%21,%22,%23,%24,%25,%26,%27,%28,%29,%30,%31,%32,%33,%34,%35,%36,%37,%38,%39,%40,%41,%42,%43,%44,%45,%46,%47,%48,%49,%50,%51,%52,%53,%54,%55,%56,%57,%58,%59,%60,%61,%62,%63}, "
    "{%64,%65,%66,%67}, %68, 1, 1, 1, 0;"
    : "=&r"(d[0]),"=&r"(d[1]),"=&r"(d[2]),"=&r"(d[3]),"=&r"(d[4]),"=&r"(d[5]),"=&r"(d[6]),"=&r"(d[7]),"=&r"(d[8]),"=&r"(d[9]),"=&r"(d[10]),"=&r"(d[11]),"=&r"(d[12]),"=&r"(d[13]),"=&r"(d[14]),"=&r"(d[15]),"=&r"(d[16]),"=&r"(d[17]),"=&r"(d[18]),"=&r"(d[19]),"=&r"(d[20]),"=&r"(d[21]),"=&r"(d[22]),"=&r"(d[23]),"=&r"(d[24]),"=&r"(d[25]),"=&r"(d[26]),"=&r"(d[27]),"=&r"(d[28]),"=&r"(d[29]),"=&r"(d[30]),"=&r"(d[31]),"=&r"(d[32]),"=&r"(d[33]),"=&r"(d[34]),"=&r"(d[35]),"=&r"(d[36]),"=&r"(d[37]),"=&r"(d[38]),"=&r"(d[39]),"=&r"(d[40]),"=&r"(d[41]),"=&r"(d[42]),"=&r"(d[43]),"=&r"(d[44]),"=&r"(d[45]),"=&r"(d[46]),"=&r"(d[47]),"=&r"(d[48]),"=&r"(d[49]),"=&r"(d[50]),"=&r"(d[51]),"=&r"(d[52]),"=&r"(d[53]),"=&r"(d[54]),"=&r"(d[55]),"=&r"(d[56]),"=&r"(d[57]),"=&r"(d[58]),"=&r"(d[59]),"=&r"(d[60]),"=&r"(d[61]),"=&r"(d[62]),"=&r"(d[63])
    : "r"(a[0]), "r"(a[1]), "r"(a[2]), "r"(a[3]), "l"(desc), "r"(c0), "r"(c1), "r"(0), "l"(dc));
}
__device__ __forceinline__ void mma_n64(float* d, const uint32_t* a, uint32_t dlo, int off, int acc) {
  asm volatile("{.reg .pred p; .reg .b32 t; .reg .b64 ds; add.u32 t, %36, %37; mov.b64 ds, {t, 0x40000040}; setp.ne.b32 p, %38, 0;\n"
    "wgmma.mma_async.sync.aligned.m64n64k16.f32.bf16.bf16 {%0,%1,%2,%3,%4,%5,%6,%7,%8,%9,%10,%11,%12,%13,%14,%15,%16,%17,%18,%19,%20,%21,%22,%23,%24,%25,%26,%27,%28,%29,%30,%31}, "
    "{%32,%33,%34,%35}, ds, p, 1, 1, 1;}"
    : "+f"(d[0]),"+f"(d[1]),"+f"(d[2]),"+f"(d[3]),"+f"(d[4]),"+f"(d[5]),"+f"(d[6]),"+f"(d[7]),"+f"(d[8]),"+f"(d[9]),"+f"(d[10]),"+f"(d[11]),"+f"(d[12]),"+f"(d[13]),"+f"(d[14]),"+f"(d[15]),"+f"(d[16]),"+f"(d[17]),"+f"(d[18]),"+f"(d[19]),"+f"(d[20]),"+f"(d[21]),"+f"(d[22]),"+f"(d[23]),"+f"(d[24]),"+f"(d[25]),"+f"(d[26]),"+f"(d[27]),"+f"(d[28]),"+f"(d[29]),"+f"(d[30]),"+f"(d[31])
    : "r"(a[0]), "r"(a[1]), "r"(a[2]), "r"(a[3]), "r"(dlo), "r"(off >> 4), "r"(acc));
}
__device__ __forceinline__ void mma_n128(float* d, const uint32_t* a, uint32_t dlo, int off, int acc) {
  asm volatile("{.reg .pred p; .reg .b32 t; .reg .b64 ds; add.u32 t, %68, %69; mov.b64 ds, {t, 0x40000040}; setp.ne.b32 p, %70, 0;\n"
    "wgmma.mma_async.sync.aligned.m64n128k16.f32.bf16.bf16 {%0,%1,%2,%3,%4,%5,%6,%7,%8,%9,%10,%11,%12,%13,%14,%15,%16,%17,%18,%19,%20,%21,%22,%23,%24,%25,%26,%27,%28,%29,%30,%31,%32,%33,%34,%35,%36,%37,%38,%39,%40,%41,%42,%43,%44,%45,%46,%47,%48,%49,%50,%51,%52,%53,%54,%55,%56,%57,%58,%59,%60,%61,%62,%63}, "
    "{%64,%65,%66,%67}, ds, p, 1, 1, 1;}"
    : "+f"(d[0]),"+f"(d[1]),"+f"(d[2]),"+f"(d[3]),"+f"(d[4]),"+f"(d[5]),"+f"(d[6]),"+f"(d[7]),"+f"(d[8]),"+f"(d[9]),"+f"(d[10]),"+f"(d[11]),"+f"(d[12]),"+f"(d[13]),"+f"(d[14]),"+f"(d[15]),"+f"(d[16]),"+f"(d[17]),"+f"(d[18]),"+f"(d[19]),"+f"(d[20]),"+f"(d[21]),"+f"(d[22]),"+f"(d[23]),"+f"(d[24]),"+f"(d[25]),"+f"(d[26]),"+f"(d[27]),"+f"(d[28]),"+f"(d[29]),"+f"(d[30]),"+f"(d[31]),"+f"(d[32]),"+f"(d[33]),"+f"(d[34]),"+f"(d[35]),"+f"(d[36]),"+f"(d[37]),"+f"(d[38]),"+f"(d[39]),"+f"(d[40]),"+f"(d[41]),"+f"(d[42]),"+f"(d[43]),"+f"(d[44]),"+f"(d[45]),"+f"(d[46]),"+f"(d[47]),"+f"(d[48]),"+f"(d[49]),"+f"(d[50]),"+f"(d[51]),"+f"(d[52]),"+f"(d[53]),"+f"(d[54]),"+f"(d[55]),"+f"(d[56]),"+f"(d[57]),"+f"(d[58]),"+f"(d[59]),"+f"(d[60]),"+f"(d[61]),"+f"(d[62]),"+f"(d[63])
    : "r"(a[0]), "r"(a[1]), "r"(a[2]), "r"(a[3]), "r"(dlo), "r"(off >> 4), "r"(acc));
}
__device__ __forceinline__ void mma_n48(float* d, const uint32_t* a, uint32_t dlo, int off, int acc) {
  asm volatile("{.reg .pred p; .reg .b32 t; .reg .b64 ds; add.u32 t, %28, %29; mov.b64 ds, {t, 0x40000040}; setp.ne.b32 p, %30, 0;\n"
    "wgmma.mma_async.sync.aligned.m64n48k16.f32.bf16.bf16 {%0,%1,%2,%3,%4,%5,%6,%7,%8,%9,%10,%11,%12,%13,%14,%15,%16,%17,%18,%19,%20,%21,%22,%23}, "
    "{%24,%25,%26,%27}, ds, p, 1, 1, 1;}"
    : "+f"(d[0]),"+f"(d[1]),"+f"(d[2]),"+f"(d[3]),"+f"(d[4]),"+f"(d[5]),"+f"(d[6]),"+f"(d[7]),"+f"(d[8]),"+f"(d[9]),"+f"(d[10]),"+f"(d[11]),"+f"(d[12]),"+f"(d[13]),"+f"(d[14]),"+f"(d[15]),"+f"(d[16]),"+f"(d[17]),"+f"(d[18]),"+f"(d[19]),"+f"(d[20]),"+f"(d[21]),"+f"(d[22]),"+f"(d[23])
    : "r"(a[0]), "r"(a[1]), "r"(a[2]), "r"(a[3]), "r"(dlo), "r"(off >> 4), "r"(acc));
}
__device__ __forceinline__ void mma_pv24(float* d, const uint32_t* a, uint32_t dlo, int off, int acc) {
  asm volatile("{.reg .pred p; .reg .b32 t; .reg .b64 ds; add.u32 t, %16, %17; mov.b64 ds, {t, 0x800}; setp.ne.b32 p, %18, 0;\n"
    "wgmma.mma_async.sync.aligned.m64n24k16.f32.f16.f16 {%0,%1,%2,%3,%4,%5,%6,%7,%8,%9,%10,%11}, "
    "{%12,%13,%14,%15}, ds, p, 1, 1, 1;}"
    : "+f"(d[0]),"+f"(d[1]),"+f"(d[2]),"+f"(d[3]),"+f"(d[4]),"+f"(d[5]),"+f"(d[6]),"+f"(d[7]),"+f"(d[8]),"+f"(d[9]),"+f"(d[10]),"+f"(d[11])
    : "r"(a[0]), "r"(a[1]), "r"(a[2]), "r"(a[3]), "r"(dlo), "r"(off >> 4), "r"(acc));
}
__device__ __forceinline__ void mma_qk256(uint32_t* d, const uint32_t* a, uint64_t desc) {
  asm volatile("wgmma.mma_async.sync.aligned.m64n256k16.f16.f16.f16 {%0,%1,%2,%3,%4,%5,%6,%7,%8,%9,%10,%11,%12,%13,%14,%15,%16,%17,%18,%19,%20,%21,%22,%23,%24,%25,%26,%27,%28,%29,%30,%31,%32,%33,%34,%35,%36,%37,%38,%39,%40,%41,%42,%43,%44,%45,%46,%47,%48,%49,%50,%51,%52,%53,%54,%55,%56,%57,%58,%59,%60,%61,%62,%63}, "
    "{%64,%65,%66,%67}, %68, 0, 1, 1, 0;"
    : "=r"(d[0]),"=r"(d[1]),"=r"(d[2]),"=r"(d[3]),"=r"(d[4]),"=r"(d[5]),"=r"(d[6]),"=r"(d[7]),"=r"(d[8]),"=r"(d[9]),"=r"(d[10]),"=r"(d[11]),"=r"(d[12]),"=r"(d[13]),"=r"(d[14]),"=r"(d[15]),"=r"(d[16]),"=r"(d[17]),"=r"(d[18]),"=r"(d[19]),"=r"(d[20]),"=r"(d[21]),"=r"(d[22]),"=r"(d[23]),"=r"(d[24]),"=r"(d[25]),"=r"(d[26]),"=r"(d[27]),"=r"(d[28]),"=r"(d[29]),"=r"(d[30]),"=r"(d[31]),"=r"(d[32]),"=r"(d[33]),"=r"(d[34]),"=r"(d[35]),"=r"(d[36]),"=r"(d[37]),"=r"(d[38]),"=r"(d[39]),"=r"(d[40]),"=r"(d[41]),"=r"(d[42]),"=r"(d[43]),"=r"(d[44]),"=r"(d[45]),"=r"(d[46]),"=r"(d[47]),"=r"(d[48]),"=r"(d[49]),"=r"(d[50]),"=r"(d[51]),"=r"(d[52]),"=r"(d[53]),"=r"(d[54]),"=r"(d[55]),"=r"(d[56]),"=r"(d[57]),"=r"(d[58]),"=r"(d[59]),"=r"(d[60]),"=r"(d[61]),"=r"(d[62]),"=r"(d[63])
    : "r"(a[0]), "r"(a[1]), "r"(a[2]), "r"(a[3]), "l"(desc));
}

__global__ void __launch_bounds__(256) k_mod(const bf16* __restrict__ c, const bf16* __restrict__ wm) {
  TS(0, 0, threadIdx.x == 0);
  pdl_trigger();
  __shared__ float red[8][32];
  const int tid = threadIdx.x, r = tid >> 2, cc = tid & 3, lane = tid & 31, w = tid >> 5;
  uint4 v[8];
#pragma unroll
  for (int i = 0; i < 8; i++) v[i] = ldg128_nc(wm + (size_t)(r + 64 * i) * (6 * D_) + blockIdx.x * 32 + cc * 8);
  if (blockIdx.x < 8) g_flags[blockIdx.x * 256 + tid] = 0;
  float acc[8];
#pragma unroll
  for (int e = 0; e < 8; e++) acc[e] = 0.f;
#pragma unroll
  for (int i = 0; i < 8; i++) {
    float cv = __bfloat162float(c[r + 64 * i]);
    float s = __bfloat162float(__float2bfloat16(cv / (1.f + __expf(-cv))));
    uint32_t u[4] = {v[i].x, v[i].y, v[i].z, v[i].w};
#pragma unroll
    for (int e = 0; e < 4; e++) { acc[2 * e] += s * bf_lo(u[e]); acc[2 * e + 1] += s * bf_hi(u[e]); }
  }
#pragma unroll
  for (int e = 0; e < 8; e++) {
    acc[e] += __shfl_xor_sync(~0u, acc[e], 4);
    acc[e] += __shfl_xor_sync(~0u, acc[e], 8);
    acc[e] += __shfl_xor_sync(~0u, acc[e], 16);
  }
  if (lane < 4) {
#pragma unroll
    for (int e = 0; e < 8; e++) red[w][lane * 8 + e] = acc[e];
  }
  __syncthreads();
  if (tid < 32) {
    float s = 0.f;
#pragma unroll
    for (int i = 0; i < 8; i++) s += red[i][tid];
    const int col = blockIdx.x * 32 + tid, seg = col >> 9;
    bf16 m = __float2bfloat16(s);
    if (seg == 1 || seg == 4) m = __float2bfloat16(1.f + __bfloat162float(m));
    g_mod[col] = m;
  }
  TS(0, 1, tid == 0);
}

constexpr int QKV_SMEM = 24 * 8192 + 2048 + 256 + 1024;
__global__ void __launch_bounds__(256, 1) k_qkv(const __grid_constant__ CUtensorMap tm_w, const bf16* __restrict__ x) {
  extern __shared__ __align__(1024) uint8_t sp[];
  const uint32_t sb = smem_u32(sp), dlo = desc_lo(sb, 8192);
  const uint32_t bars = sb + 24 * 8192 + 2048;
  const int tid = threadIdx.x, lane = tid & 31, w = tid >> 5, g = lane >> 2, q = lane & 3;
  const int nt = blockIdx.x & 7, rb16 = (blockIdx.x >> 3) * 8 + w;
  TS(1, 0, tid == 0);
  pdl_trigger();
  if (tid == 0) {
    for (int i = 0; i < 6; i++) mbar_init(bars + 8 * i, 1);
    asm volatile("fence.mbarrier_init.release.cluster;" ::: "memory");
    for (int i = 0; i < 6; i++) {
      mbar_expect(bars + 8 * i, 4 * 8192);
      for (int kb = 0; kb < 4; kb++)
        tma5d(sb + (i * 4 + kb) * 8192, &tm_w, nt * 192 + (i >> 1) * 64, ((i & 1) * 4 + kb) * 2, bars + 8 * i);
    }
  }
  uint32_t a[128];
  {
    const bf16* x0 = x + (size_t)(rb16 * 16 + g) * D_ + q * 8;
#pragma unroll
    for (int b = 0; b < 16; b++) {
      uint4 u = ldg128_nc(x0 + b * 32), v = ldg128_nc(x0 + 8 * D_ + b * 32);
      a[8 * b] = u.x; a[8 * b + 2] = u.y; a[8 * b + 4] = u.z; a[8 * b + 6] = u.w;
      a[8 * b + 1] = v.x; a[8 * b + 3] = v.y; a[8 * b + 5] = v.z; a[8 * b + 7] = v.w;
    }
    TS(1, 1, tid == 0 && a[127] != 0x12345);
    float s[4] = {0.f, 0.f, 0.f, 0.f};
#pragma unroll
    for (int i = 0; i < 128; i++) { s[i & 1] += bf_lo(a[i]); s[2 + (i & 1)] += bf_hi(a[i]); }
    float m0 = s[0] + s[2], m1 = s[1] + s[3];
    m0 += __shfl_xor_sync(~0u, m0, 1); m1 += __shfl_xor_sync(~0u, m1, 1);
    m0 += __shfl_xor_sync(~0u, m0, 2); m1 += __shfl_xor_sync(~0u, m1, 2);
    m0 *= -1.f / D_; m1 *= -1.f / D_;
    const uint32_t one = 0x3F803F80u, nm0 = pack_bf16(m0, m0), nm1 = pack_bf16(m1, m1);
    s[0] = s[1] = s[2] = s[3] = 0.f;
#pragma unroll
    for (int i = 0; i < 128; i++) {
      a[i] = bf_fma2(a[i], one, (i & 1) ? nm1 : nm0);
      float lo = bf_lo(a[i]), hi = bf_hi(a[i]);
      s[i & 1] += lo * lo; s[2 + (i & 1)] += hi * hi;
    }
    float v0 = s[0] + s[2], v1 = s[1] + s[3];
    v0 += __shfl_xor_sync(~0u, v0, 1); v1 += __shfl_xor_sync(~0u, v1, 1);
    v0 += __shfl_xor_sync(~0u, v0, 2); v1 += __shfl_xor_sync(~0u, v1, 2);
    v0 = rsqrtf(v0 * (1.f / D_) + 1e-5f); v1 = rsqrtf(v1 * (1.f / D_) + 1e-5f);
    const uint32_t r0 = pack_bf16(v0, v0), r1 = pack_bf16(v1, v1);
#pragma unroll
    for (int i = 0; i < 128; i++) a[i] = bf_fma2(a[i], (i & 1) ? r1 : r0, 0x80008000u);
  }
  TS(1, 2, tid == 0 && a[127] != 0x12345);
  pdl_wait();
  TS(1, 3, tid == 0);
  if (tid < 128) *(uint4*)(sp + 24 * 8192 + tid * 16) = ldg128((const uint8_t*)g_mod + tid * 16);
  __syncthreads();
  TS(1, 4, tid == 0);
  float acc[2][32];
#pragma unroll
  for (int kb = 0; kb < 8; kb++) {
#pragma unroll
    for (int b = 2 * kb; b < 2 * kb + 2; b++) {
      uint4 sa = *(const uint4*)(sp + 24 * 8192 + b * 64 + q * 16), ca = *(const uint4*)(sp + 24 * 8192 + 1024 + b * 64 + q * 16);
      uint32_t su[4] = {sa.x, sa.y, sa.z, sa.w}, cu[4] = {ca.x, ca.y, ca.z, ca.w};
#pragma unroll
      for (int j = 0; j < 8; j++) a[8 * b + j] = bf_fma2(a[8 * b + j], cu[j >> 1], su[j >> 1]);
    }
    if ((kb & 3) == 0) mbar_wait(bars + 8 * (kb >> 2), 0);
    wg_fence();
#pragma unroll
    for (int ks = 0; ks < 4; ks++) MMA(mma_n64, kb * 8192 + ks * 2048, kb | ks, acc[0], a + (kb * 4 + ks) * 4, dlo);
  }
  wg_commit();
#pragma unroll
  for (int p = 0; p < 3; p++) {
    if (p < 2) {
      mbar_wait(bars + 8 * (2 * p + 2), 0);
      mbar_wait(bars + 8 * (2 * p + 3), 0);
      wg_fence();
#pragma unroll
      for (int ks = 0; ks < 32; ks++) MMA(mma_n64, (p + 1) * 65536 + ks * 2048, ks, acc[(p + 1) & 1], a + ks * 4, dlo);
      wg_commit();
      wg_wait<1>();
    } else {
      wg_wait<0>();
    }
    float* d = acc[p & 1];
    reg_fence<32>(d);
    TS(1, 5 + p, tid == 0);
    const int col = nt * 192 + p * 64, sec = col >> 9, h0 = (col & 511) >> 4;
    if (sec == 0) {
      const float sc = 0.25f * 1.4426950408889634f;
#pragma unroll
      for (int hh = 0; hh < 4; hh++)
        g_q[((h0 + hh) * 128 + rb16) * 32 + lane] =
            make_uint4(pack_f16(d[8 * hh] * sc, d[8 * hh + 1] * sc), pack_f16(d[8 * hh + 2] * sc, d[8 * hh + 3] * sc),
                       pack_f16(d[8 * hh + 4] * sc, d[8 * hh + 5] * sc), pack_f16(d[8 * hh + 6] * sc, d[8 * hh + 7] * sc));
    } else {
      uint32_t* dst = (uint32_t*)(sec == 1 ? g_k : g_v) + (size_t)(h0 * 2 * S_ + rb16 * 16) * 4 + lane;
      const float k0 = (sec == 1 && poly_grp(2 * rb16)) ? 1.f / 512 : 1.f, k1 = (sec == 1 && poly_grp(2 * rb16 + 1)) ? 1.f / 512 : 1.f;
#pragma unroll
      for (int jj = 0; jj < 8; jj++) {
        dst[jj * S_ * 4] = pack_f16(d[4 * jj] * k0, d[4 * jj + 1] * k0);
        dst[jj * S_ * 4 + 32] = pack_f16(d[4 * jj + 2] * k1, d[4 * jj + 3] * k1);
      }
    }
  }
  TS(1, 8, tid == 0);
}

__device__ __forceinline__ uint32_t h_max(uint32_t a, uint32_t b) { uint32_t r; asm("max.f16x2 %0, %1, %2;" : "=r"(r) : "r"(a), "r"(b)); return r; }
__device__ __forceinline__ uint32_t h_add(uint32_t a, uint32_t b) { uint32_t r; asm("add.rn.f16x2 %0, %1, %2;" : "=r"(r) : "r"(a), "r"(b)); return r; }
__device__ __forceinline__ uint32_t h_sub(uint32_t a, uint32_t b) { uint32_t r; asm("sub.rn.f16x2 %0, %1, %2;" : "=r"(r) : "r"(a), "r"(b)); return r; }
__device__ __forceinline__ uint32_t h_mul(uint32_t a, uint32_t b) { uint32_t r; asm("mul.rn.f16x2 %0, %1, %2;" : "=r"(r) : "r"(a), "r"(b)); return r; }
__device__ __forceinline__ uint32_t h_fma(uint32_t a, uint32_t b, uint32_t c) { uint32_t r; asm("fma.rn.f16x2 %0, %1, %2, %3;" : "=r"(r) : "r"(a), "r"(b), "r"(c)); return r; }
__device__ __forceinline__ uint32_t h_fma_relu(uint32_t a, uint32_t b, uint32_t c) { uint32_t r; asm("fma.rn.relu.f16x2 %0, %1, %2, %3;" : "=r"(r) : "r"(a), "r"(b), "r"(c)); return r; }
__device__ __forceinline__ uint32_t h_ex2(uint32_t a) { uint32_t r; asm("ex2.approx.f16x2 %0, %1;" : "=r"(r) : "r"(a)); return r; }
__device__ __forceinline__ float h_lo(uint32_t v) { return __half2float(__ushort_as_half((unsigned short)(v & 0xffff))); }
__device__ __forceinline__ float h_hi(uint32_t v) { return __half2float(__ushort_as_half((unsigned short)(v >> 16))); }

__device__ __forceinline__ uint32_t exp2_fma(uint32_t u) {
  const uint32_t n = h_fma_relu(u, 0x02000200u, 0u);
  const uint32_t f = h_fma(n, 0xF800F800u, u);
  uint32_t p = h_fma(f, 0x630D630Du, 0x47C047C0u);
  p = h_fma(p, f, 0x298C298Cu);
  p = h_fma_relu(p, f, 0x08000800u);
  return p + (n << 10);
}

#define TOP 5
__device__ __forceinline__ bool h_gt(uint32_t a, uint32_t b) {
  uint32_t r; asm("{.reg .pred p, q; setp.gt.f16x2 p|q, %1, %2; or.pred p, p, q; selp.u32 %0, 1, 0, p;}" : "=r"(r) : "r"(a), "r"(b)); return r;
}
__device__ __forceinline__ void block_max(const uint32_t* s, uint32_t* mx) {
  uint32_t pend[4]; int st[4] = {0, 0, 0, 0};
#pragma unroll
  for (int i = 0; i < 64; i++) {
    const int k = (poly_grp(i >> 1) ? 2 : 0) + (i & 1);
    if (st[k] == 0) { mx[k] = s[i]; st[k] = 1; }
    else if (st[k] == 1) { pend[k] = s[i]; st[k] = 2; }
    else { mx[k] = h_max(h_max(mx[k], pend[k]), s[i]); st[k] = 1; }
  }
#pragma unroll
  for (int k = 0; k < 4; k++) if (st[k] == 2) mx[k] = h_max(mx[k], pend[k]);
}
__device__ __forceinline__ uint32_t row_max(const uint32_t* mx, uint32_t bias) {
  const uint32_t m0 = h_max(mx[0], h_fma(mx[2], 0x60006000u, bias)), m1 = h_max(mx[1], h_fma(mx[3], 0x60006000u, bias));
  uint32_t M = h_max(__byte_perm(m0, m1, 0x5410), __byte_perm(m0, m1, 0x7632));
  M = h_max(M, __shfl_xor_sync(~0u, M, 1));
  return h_max(M, __shfl_xor_sync(~0u, M, 2));
}
constexpr int ATT_THREADS = 512;
constexpr int ATT_SMEM = 5 * 32768 + 4096 + 128 + 1024;
__global__ void __launch_bounds__(512, 1) k_attn(const bf16* __restrict__ wo, const bf16* __restrict__ w1,
                                                 const bf16* __restrict__ w3, const bf16* __restrict__ w2) {
  extern __shared__ __align__(1024) uint8_t sp[];
  const uint32_t sb = smem_u32(sp);
  const uint32_t bars = sb + 5 * 32768 + 4096;
  const int tid = threadIdx.x, lane = tid & 31, w = tid >> 5;
  const int head = blockIdx.x >> 2, quarter = blockIdx.x & 3;
  TS(2, 0, tid == 0);
  if (tid == 0) {
    for (int i = 0; i < 8; i++) mbar_init(bars + 8 * i, 1);
    asm volatile("fence.mbarrier_init.release.cluster;" ::: "memory");
  }
#pragma unroll
  for (int i = 0; i < 4; i++) *(uint4*)(sp + 4 * 32768 + (i * 512 + tid) * 16) = make_uint4(0x3C003C00u, 0x3C003C00u, 0x3C003C00u, 0x3C003C00u);
  if (tid < 256) *(uint4*)(sp + 5 * 32768 + tid * 16) = make_uint4(poly_grp(tid >> 3) ? 0x26801800u : 0x00003C00u, 0, 0, 0);
  asm volatile("fence.proxy.async.shared::cta;" ::: "memory");
  __syncthreads();
  pdl_wait();
  TS(2, 1, tid == 0);
  if (tid == 0) {
    for (int i = 0; i < 8; i++) {
      mbar_expect(bars + 8 * i, 16384);
      bulk_g2s(sb + i * 4096, g_k + (head * 2) * S_ + i * 256, 4096, bars + 8 * i);
      bulk_g2s(sb + 32768 + i * 4096, g_k + (head * 2 + 1) * S_ + i * 256, 4096, bars + 8 * i);
      bulk_g2s(sb + 65536 + i * 4096, g_v + (head * 2) * S_ + i * 256, 4096, bars + 8 * i);
      bulk_g2s(sb + 98304 + i * 4096, g_v + (head * 2 + 1) * S_ + i * 256, 4096, bars + 8 * i);
    }
  }
  pdl_trigger();
  if (tid == 64) {
    l2_prefetch((const uint8_t*)wo + blockIdx.x * 4096, 4096);
    l2_prefetch((const uint8_t*)w1 + blockIdx.x * 11008, 11008);
    l2_prefetch((const uint8_t*)w3 + blockIdx.x * 11008, 11008);
    l2_prefetch((const uint8_t*)w2 + blockIdx.x * 11008, 11008);
  }
  const uint64_t dk0 = desc_plain(sb, 32768, 128);
  const uint64_t dc0 = desc_plain(sb + 5 * 32768, 0, 128);
  const uint32_t dv0 = desc_lo(sb + 65536, 128);
#pragma unroll 1
  for (int t = 0; t < 2; t++) {
    const int rb16 = quarter * 32 + (w >> 2) * 8 + t * 4 + (w & 3);
    uint32_t qf[4];
    { uint4 u = ldg128(g_q + (head * 128 + rb16) * 32 + lane); qf[0] = u.x; qf[1] = u.y; qf[2] = u.z; qf[3] = u.w; }
    float o[12];
#pragma unroll
    for (int i = 0; i < 12; i++) o[i] = 0.f;
    uint32_t s[64], mx[4];
    if (t == 0) mbar_wait(bars, 0);
    wg_fence();
    mma_qk256(s, qf, dk0);
    wg_commit();
    wg_wait<0>();
    reg_fence<64>(s);
    TS(2, 2, tid == 0 && t == 0);
    block_max(s, mx);
    uint32_t c = h_sub(h_sub(0x66006600u + TOP * 0x10001u, row_max(mx, 0u)), 0x66006600u);
    uint32_t ca0 = (lane & 3) ? 0u : __byte_perm(c, 0x3C00u, 0x5410), ca1 = (lane & 3) ? 0u : __byte_perm(c, 0x3C00u, 0x5432);
#pragma unroll 1
    for (int kb = 0; kb < 8; kb++) {
      if (t == 0) mbar_wait(bars + 8 * kb, 0);
      wg_fence();
      mma_qkc256(s, ca0, ca1, dc0, qf, dk0 + kb * 256);
      wg_commit();
      wg_wait<0>();
      reg_fence<64>(s);
      block_max(s, mx);
      if (__any_sync(~0u, h_gt(h_max(h_max(mx[0], mx[1]), h_fma(h_max(mx[2], mx[3]), 0x60006000u, 0xCA80CA80u)), 0x4BF04BF0u))) {
        const uint32_t up = h_max(h_sub(h_add(row_max(mx, 0xCA80CA80u), 0x66006600u - TOP * 0x10001u), 0x66006600u), 0u);
        const uint32_t cn = h_sub(c, up), dl = h_sub(cn, c), dp = h_mul(dl, 0x18001800u);
        c = cn;
        ca0 = (lane & 3) ? 0u : __byte_perm(c, 0x3C00u, 0x5410); ca1 = (lane & 3) ? 0u : __byte_perm(c, 0x3C00u, 0x5432);
        const float a0 = ex2f(h_lo(dl)), a1 = ex2f(h_hi(dl));
        const uint32_t d0 = __byte_perm(dl, dl, 0x1010), d1 = __byte_perm(dl, dl, 0x3232);
        const uint32_t p0 = __byte_perm(dp, dp, 0x1010), p1 = __byte_perm(dp, dp, 0x3232);
        o[0] *= a0; o[1] *= a0; o[4] *= a0; o[5] *= a0; o[8] *= a0;
        o[2] *= a1; o[3] *= a1; o[6] *= a1; o[7] *= a1; o[10] *= a1;
#pragma unroll
        for (int i = 0; i < 64; i++) s[i] = h_add(s[i], poly_grp(i >> 1) ? ((i & 1) ? p1 : p0) : ((i & 1) ? d1 : d0));
      }
#pragma unroll
      for (int grp = 0; grp < 4; grp++) {
#pragma unroll
        for (int i = grp * 16; i < grp * 16 + 16; i++)
          s[i] = poly_grp(i >> 1) ? exp2_fma(s[i]) : h_ex2(s[i]);
        wg_fence();
#pragma unroll
        for (int ks = grp * 4; ks < grp * 4 + 4; ks++) mma_pv24(o, s + ks * 4, dv0 + kb * 256, ks * 256, 1);
      }
      wg_commit();
      wg_wait<0>();
      reg_fence<12>(o);
    }
    TS(2, 3 + t, tid == 0);
    TS(2, 5 + t, tid == 384);
    const float i0 = 1.f / o[8], i1 = 1.f / o[10];
    g_attn[(rb16 * 32 + head) * 32 + lane] = make_uint4(pack_bf16(o[0] * i0, o[1] * i0), pack_bf16(o[2] * i1, o[3] * i1),
                                                        pack_bf16(o[4] * i0, o[5] * i0), pack_bf16(o[6] * i1, o[7] * i1));
  }
}

__device__ float4 g_stats[128 * 16 * 4];
constexpr int NST = 13, STB = 16384;
constexpr int FFN_SMEM = NST * STB + 4096 + 512 + 1024;

__device__ __forceinline__ void flag_signal(unsigned* f, int lane) {
  __syncwarp();
  if (lane == 0) asm volatile("red.release.gpu.global.add.u32 [%0], 1;" ::"l"(f) : "memory");
}
__device__ __forceinline__ void flag_wait(const unsigned* f, int lane) {
  if (lane == 0) {
    unsigned v, n = 0;
    do {
      asm volatile("ld.acquire.gpu.global.u32 %0, [%1];" : "=r"(v) : "l"(f) : "memory");
      if (++n > (1u << 24)) __trap();
    } while (v < 8);
  }
  __syncwarp();
}
__device__ __forceinline__ float silu_mul(float g, float u) { return g * u * rcpf(1.f + ex2f(g * -1.4426950408889634f)); }

__global__ void __launch_bounds__(384, 1) __cluster_dims__(2, 1, 1)
k_ffn(const __grid_constant__ CUtensorMap tm_wo, const __grid_constant__ CUtensorMap tm_w1, const __grid_constant__ CUtensorMap tm_w3,
      const __grid_constant__ CUtensorMap tm_w2, const bf16* __restrict__ x, bf16* __restrict__ out) {
  extern __shared__ __align__(1024) uint8_t sp[];
  const uint32_t sb = smem_u32(sp), dlo = desc_lo(sb, 8192);
  const uint32_t bfull = sb + NST * STB + 4096, bempty = bfull + 8 * NST, bpeer = bempty + 8 * NST, bx = bpeer + 8;
  const int tid = threadIdx.x, lane = tid & 31, w = tid >> 5;
  const int j = blockIdx.x & 7, rb = blockIdx.x >> 3, kh = j & 1;
  TS(3, 0, tid == 0);
  if (tid == 0) {
    for (int i = 0; i < NST; i++) { mbar_init(bfull + 8 * i, 1); mbar_init(bempty + 8 * i, 8); }
    mbar_init(bpeer, 8);
    for (int i = 0; i < 8; i++) { mbar_init(bx + 8 * i, 1); }
    asm volatile("fence.mbarrier_init.release.cluster;" ::: "memory");
    for (int i = 0; i < 8; i++) mbar_expect(bx + 8 * i, 4096);
  }
  if (tid < 256) *(uint4*)(sp + NST * STB + tid * 16) = ldg128((const uint8_t*)g_mod + 2048 + tid * 16);
  __syncthreads();
  asm volatile("barrier.cluster.arrive.release.aligned;" ::: "memory");
  if (w >= 8) {
    asm volatile("setmaxnreg.dec.sync.aligned.u32 24;");
    if (tid == 256) {
      int slot = 0, ph = 1;
#pragma unroll 1
      for (int st = 0; st < 39; st++) {
        const CUtensorMap *m0, *m1; int x0, y0, x1, y1;
        if (st < 4) { m0 = m1 = &tm_wo; x0 = x1 = j * 64; y0 = st * 128; y1 = y0 + 64; }
        else if (st < 28) { m0 = &tm_w1; m1 = &tm_w3; x0 = x1 = j * 176 + ((st - 4) >> 3) * 64; y0 = y1 = ((st - 4) & 7) * 64; }
        else { m0 = m1 = &tm_w2; x0 = (j >> 1) * 128; x1 = x0 + 64; y0 = y1 = kh * 688 + (st - 28) * 64; }
        mbar_wait(bempty + 8 * slot, ph);
        mbar_expect(bfull + 8 * slot, STB);
        tma2d(sb + slot * STB, m0, x0, y0, bfull + 8 * slot);
        tma2d(sb + slot * STB + 8192, m1, x1, y1, bfull + 8 * slot);
        if (++slot == NST) { slot = 0; ph ^= 1; }
      }
    }
    __syncwarp();
    asm volatile("barrier.cluster.wait.acquire.aligned;" ::: "memory");
  } else {
    asm volatile("setmaxnreg.inc.sync.aligned.u32 240;");
    const int g = lane >> 2, q = lane & 3, rb16 = rb * 8 + w;
    const uint32_t* smod = (const uint32_t*)(sp + NST * STB);
    uint32_t a[128];
    float acc[64];
    uint32_t xr[16];
    {
      const uint32_t* x0 = (const uint32_t*)(x + (size_t)(rb16 * 16 + g) * D_ + j * 64) + q;
#pragma unroll
      for (int i = 0; i < 8; i++) { xr[2 * i] = __ldg(x0 + i * 4); xr[2 * i + 1] = __ldg(x0 + 8 * D_ / 2 + i * 4); }
    }
    asm volatile("barrier.cluster.wait.acquire.aligned;" ::: "memory");
    TS(3, 1, tid == 0);
    pdl_wait();
    TS(3, 2, tid == 0);
#pragma unroll
    for (int i = 0; i < 32; i++) { uint4 u = ldg128(g_attn + (rb16 * 32 + i) * 32 + lane); a[4 * i] = u.x; a[4 * i + 1] = u.y; a[4 * i + 2] = u.z; a[4 * i + 3] = u.w; }
#pragma unroll
    for (int st = 0; st < 4; st++) {
      mbar_wait(bfull + 8 * st, 0);
      wg_fence();
#pragma unroll
      for (int ks = 0; ks < 8; ks++) MMA(mma_n64, st * STB + ks * 2048, st | ks, acc, a + (st * 8 + ks) * 4, dlo);
    }
    wg_commit();
    wg_wait<0>();
    reg_fence<32>(acc);
    TS(3, 3, tid == 0);
    if (lane < 4) mbar_arrive(bempty + 8 * lane);
    {
      float s0 = 0.f, s1 = 0.f;
#pragma unroll
      for (int i = 0; i < 8; i++) {
        const uint32_t ga = smod[j * 32 + i * 4 + q];
        xr[2 * i] = pack_bf16(bf_lo(xr[2 * i]) + bf_lo(ga) * acc[4 * i], bf_hi(xr[2 * i]) + bf_hi(ga) * acc[4 * i + 1]);
        xr[2 * i + 1] = pack_bf16(bf_lo(xr[2 * i + 1]) + bf_lo(ga) * acc[4 * i + 2], bf_hi(xr[2 * i + 1]) + bf_hi(ga) * acc[4 * i + 3]);
        s0 += bf_lo(xr[2 * i]) + bf_hi(xr[2 * i]); s1 += bf_lo(xr[2 * i + 1]) + bf_hi(xr[2 * i + 1]);
      }
#pragma unroll
      for (int i = 0; i < 4; i++) g_x1[(rb16 * 32 + j * 4 + i) * 32 + lane] = make_uint4(xr[4 * i], xr[4 * i + 1], xr[4 * i + 2], xr[4 * i + 3]);
      s0 += __shfl_xor_sync(~0u, s0, 1); s1 += __shfl_xor_sync(~0u, s1, 1);
      s0 += __shfl_xor_sync(~0u, s0, 2); s1 += __shfl_xor_sync(~0u, s1, 2);
      s0 *= 1.f / 64; s1 *= 1.f / 64;
      float v0 = 0.f, v1 = 0.f;
#pragma unroll
      for (int i = 0; i < 8; i++) {
        float d = bf_lo(xr[2 * i]) - s0; v0 += d * d; d = bf_hi(xr[2 * i]) - s0; v0 += d * d;
        d = bf_lo(xr[2 * i + 1]) - s1; v1 += d * d; d = bf_hi(xr[2 * i + 1]) - s1; v1 += d * d;
      }
      v0 += __shfl_xor_sync(~0u, v0, 1); v1 += __shfl_xor_sync(~0u, v1, 1);
      v0 += __shfl_xor_sync(~0u, v0, 2); v1 += __shfl_xor_sync(~0u, v1, 2);
      if (q < 2) ((float2*)g_stats)[(rb16 * 16 + g + q * 8) * 8 + j] = q ? make_float2(s1, v1) : make_float2(s0, v0);
    }
    flag_signal(g_flags + rb16 * 8, lane);
    TS(3, 4, tid == 0);
    flag_wait(g_flags + rb16 * 8, lane);
    TS(3, 5, tid == 0);
    uint32_t r0, r1, n0, n1;
    {
      uint4 t0 = ldg128(g_stats + (rb16 * 16 + g) * 4 + q), t1 = ldg128(g_stats + (rb16 * 16 + g + 8) * 4 + q);
#pragma unroll
      for (int i = 0; i < 32; i++) { uint4 u = ldg128(g_x1 + (rb16 * 32 + i) * 32 + lane); a[4 * i] = u.x; a[4 * i + 1] = u.y; a[4 * i + 2] = u.z; a[4 * i + 3] = u.w; }
      float m0 = __uint_as_float(t0.x) + __uint_as_float(t0.z), m1 = __uint_as_float(t1.x) + __uint_as_float(t1.z);
      m0 += __shfl_xor_sync(~0u, m0, 1); m1 += __shfl_xor_sync(~0u, m1, 1);
      m0 += __shfl_xor_sync(~0u, m0, 2); m1 += __shfl_xor_sync(~0u, m1, 2);
      m0 *= 0.125f; m1 *= 0.125f;
      float d0 = __uint_as_float(t0.x) - m0, d1 = __uint_as_float(t0.z) - m0;
      float v0 = __uint_as_float(t0.y) + __uint_as_float(t0.w) + 64.f * (d0 * d0 + d1 * d1);
      d0 = __uint_as_float(t1.x) - m1; d1 = __uint_as_float(t1.z) - m1;
      float v1 = __uint_as_float(t1.y) + __uint_as_float(t1.w) + 64.f * (d0 * d0 + d1 * d1);
      v0 += __shfl_xor_sync(~0u, v0, 1); v1 += __shfl_xor_sync(~0u, v1, 1);
      v0 += __shfl_xor_sync(~0u, v0, 2); v1 += __shfl_xor_sync(~0u, v1, 2);
      v0 = rsqrtf(v0 * (1.f / D_) + 1e-5f); v1 = rsqrtf(v1 * (1.f / D_) + 1e-5f);
      r0 = pack_bf16(v0, v0); r1 = pack_bf16(v1, v1);
      m0 *= -bf_lo(r0); m1 *= -bf_lo(r1);
      n0 = pack_bf16(m0, m0); n1 = pack_bf16(m1, m1);
    }
#pragma unroll
    for (int p = 0; p < 3; p++) {
      float g48[24], u48[24];
#pragma unroll
      for (int kb = 0; kb < 8; kb++) {
        const int st = 4 + p * 8 + kb, slot = st % NST;
        if (p == 0) {
#pragma unroll
          for (int i = kb * 8; i < kb * 8 + 8; i++) {
            const uint32_t sv = smod[256 + i * 4 + q], cv = smod[512 + i * 4 + q];
            a[2 * i] = bf_fma2(bf_fma2(a[2 * i], r0, n0), cv, sv);
            a[2 * i + 1] = bf_fma2(bf_fma2(a[2 * i + 1], r1, n1), cv, sv);
          }
        }
        mbar_wait(bfull + 8 * slot, (st / NST) & 1);
        wg_fence();
#pragma unroll
        for (int ks = 0; ks < 4; ks++) {
          if (p < 2) MMA(mma_n128, slot * STB + ks * 2048, kb | ks, acc, a + (kb * 4 + ks) * 4, dlo);
          else {
            MMA(mma_n48, slot * STB + ks * 2048, kb | ks, g48, a + (kb * 4 + ks) * 4, dlo);
            MMA(mma_n48, slot * STB + 8192 + ks * 2048, kb | ks, u48, a + (kb * 4 + ks) * 4, dlo);
          }
        }
        wg_commit();
        if (kb > 0) { wg_wait<1>(); if (lane == 0) mbar_arrive(bempty + 8 * ((st - 1) % NST)); }
      }
      wg_wait<0>();
      if (p < 2) reg_fence<64>(acc); else { reg_fence<24>(g48); reg_fence<24>(u48); }
      TS(3, 6 + p, tid == 0);
      if (lane == 0) {
        mbar_arrive(bempty + 8 * ((4 + p * 8 + 7) % NST));
        if (p == 2) {
          uint32_t ra; asm volatile("mapa.shared::cluster.u32 %0, %1, %2;" : "=r"(ra) : "r"(bpeer), "r"(kh ^ 1));
          asm volatile("mbarrier.arrive.shared::cluster.b64 _, [%0];" ::"r"(ra) : "memory");
        }
      }
#pragma unroll
      for (int ks = 0; ks < (p < 2 ? 4 : 3); ks++) {
        const int kk = j * 11 + p * 4 + ks;
        const float* gt = (p < 2 ? acc : g48) + 8 * ks; const float* up = (p < 2 ? acc + 32 : u48) + 8 * ks;
        uint4 u = make_uint4(pack_bf16(silu_mul(gt[0], up[0]), silu_mul(gt[1], up[1])), pack_bf16(silu_mul(gt[2], up[2]), silu_mul(gt[3], up[3])),
                             pack_bf16(silu_mul(gt[4], up[4]), silu_mul(gt[5], up[5])), pack_bf16(silu_mul(gt[6], up[6]), silu_mul(gt[7], up[7])));
        if (kk < KS_F) g_act[(rb16 * KS_F + kk) * 32 + lane] = u;
      }
    }
    flag_signal(g_flags + 1024 + rb16 * 8, lane);
    TS(3, 9, tid == 0);
    flag_wait(g_flags + 1024 + rb16 * 8, lane);
    TS(3, 10, tid == 0);
    float acc3[64];
    const uint4* ap = g_act + (rb16 * KS_F + kh * 43) * 32 + lane;
#pragma unroll
    for (int i = 0; i < 32; i++) { uint4 u = ldg128(ap + i * 32); a[4 * i] = u.x; a[4 * i + 1] = u.y; a[4 * i + 2] = u.z; a[4 * i + 3] = u.w; }
#pragma unroll
    for (int kb = 0; kb < 11; kb++) {
      const int slot = (28 + kb) % NST;
      mbar_wait(bfull + 8 * slot, 0);
      wg_fence();
#pragma unroll
      for (int ks = 0; ks < (kb < 10 ? 4 : 3); ks++)
        MMA(mma_n128, slot * STB + ks * 2048, kb | ks, acc3, a + ((kb * 4 + ks) & 31) * 4, dlo);
      wg_commit();
      if (kb == 2) {
        wg_wait<0>();
        reg_fence<64>(acc3);
        TS(3, 11, tid == 0);
#pragma unroll
        for (int i = 0; i < 11; i++) { uint4 u = ldg128(ap + (32 + i) * 32); a[4 * i] = u.x; a[4 * i + 1] = u.y; a[4 * i + 2] = u.z; a[4 * i + 3] = u.w; }
      }
    }
#pragma unroll
    for (int i = 0; i < 4; i++) { uint4 u = ldg128(g_x1 + (rb16 * 32 + j * 4 + i) * 32 + lane); xr[4 * i] = u.x; xr[4 * i + 1] = u.y; xr[4 * i + 2] = u.z; xr[4 * i + 3] = u.w; }
    mbar_wait_cluster(bpeer, 0);
    wg_wait<0>();
    reg_fence<64>(acc3);
    TS(3, 12, tid == 0);
    {
      uint32_t ra, rbar;
      asm volatile("mapa.shared::cluster.u32 %0, %1, %2;" : "=r"(ra) : "r"(sb + tid * 16), "r"(kh ^ 1));
      asm volatile("mapa.shared::cluster.u32 %0, %1, %2;" : "=r"(rbar) : "r"(bx + 8 * w), "r"(kh ^ 1));
#pragma unroll
      for (int i = 0; i < 8; i++) {
        const float s0 = kh ? acc3[4 * i] : acc3[32 + 4 * i], s1 = kh ? acc3[4 * i + 1] : acc3[33 + 4 * i];
        const float s2 = kh ? acc3[4 * i + 2] : acc3[34 + 4 * i], s3 = kh ? acc3[4 * i + 3] : acc3[35 + 4 * i];
        asm volatile("st.async.weak.shared::cluster.mbarrier::complete_tx::bytes.v4.f32 [%0], {%1,%2,%3,%4}, [%5];"
                     ::"r"(ra + i * 4096), "f"(s0), "f"(s1), "f"(s2), "f"(s3), "r"(rbar) : "memory");
      }
    }
    mbar_wait_cluster(bx + 8 * w, 0);
    TS(3, 13, tid == 0);
    uint32_t* o0 = (uint32_t*)(out + (size_t)(rb16 * 16 + g) * D_ + j * 64) + q;
#pragma unroll
    for (int i = 0; i < 8; i++) {
      const float4 pv = *(const float4*)(sp + i * 4096 + tid * 16);
      const uint32_t gb = smod[768 + j * 32 + i * 4 + q];
      const float s0 = (kh ? acc3[32 + 4 * i] : acc3[4 * i]) + pv.x, s1 = (kh ? acc3[33 + 4 * i] : acc3[4 * i + 1]) + pv.y;
      const float s2 = (kh ? acc3[34 + 4 * i] : acc3[4 * i + 2]) + pv.z, s3 = (kh ? acc3[35 + 4 * i] : acc3[4 * i + 3]) + pv.w;
      o0[i * 4] = pack_bf16(bf_lo(xr[2 * i]) + bf_lo(gb) * s0, bf_hi(xr[2 * i]) + bf_hi(gb) * s1);
      o0[8 * D_ / 2 + i * 4] = pack_bf16(bf_lo(xr[2 * i + 1]) + bf_lo(gb) * s2, bf_hi(xr[2 * i + 1]) + bf_hi(gb) * s3);
    }
    TS(3, 14, tid == 0);
  }
}

typedef CUresult (*EncodeFn)(CUtensorMap*, CUtensorMapDataType, cuuint32_t, void*, const cuuint64_t*, const cuuint64_t*,
                             const cuuint32_t*, const cuuint32_t*, CUtensorMapInterleave, CUtensorMapSwizzle,
                             CUtensorMapL2promotion, CUtensorMapFloatOOBfill);
static void make_map(EncodeFn enc, CUtensorMap* m, const void* p, int rank, const cuuint64_t* dims, const cuuint64_t* strides, const cuuint32_t* box) {
  const cuuint32_t es[5] = {1, 1, 1, 1, 1};
  enc(m, CU_TENSOR_MAP_DATA_TYPE_BFLOAT16, rank, (void*)p, dims, strides, box, es, CU_TENSOR_MAP_INTERLEAVE_NONE,
      CU_TENSOR_MAP_SWIZZLE_128B, CU_TENSOR_MAP_L2_PROMOTION_L2_256B, CU_TENSOR_MAP_FLOAT_OOB_FILL_NONE);
}
static void make_map2(EncodeFn enc, CUtensorMap* m, const void* p, int cols, int rows) {
  const cuuint64_t dims[2] = {(cuuint64_t)cols, (cuuint64_t)rows}, st[1] = {(cuuint64_t)cols * 2};
  const cuuint32_t box[2] = {64, 64};
  make_map(enc, m, p, 2, dims, st, box);
}
template <typename... KA, typename... A>
static void launch(void (*k)(KA...), int grid, int block, int smem, bool pdl, A... args) {
  cudaLaunchConfig_t cfg = {};
  cfg.gridDim = dim3(grid); cfg.blockDim = dim3(block); cfg.dynamicSmemBytes = smem; cfg.stream = cudaStreamPerThread;
  cudaLaunchAttribute at[1];
  at[0].id = cudaLaunchAttributeProgrammaticStreamSerialization;
  at[0].val.programmaticStreamSerializationAllowed = 1;
  cfg.attrs = at; cfg.numAttrs = pdl ? 1 : 0;
  cudaLaunchKernelEx(&cfg, k, KA(args)...);
}

extern "C" void kernel_launch(void* const* d_in, const int* in_sizes, int n_in, void* d_out, int out_size) {
  const bf16 *x = (const bf16*)d_in[0], *wqkv = (const bf16*)d_in[1], *wo = (const bf16*)d_in[2];
  const bf16 *w1 = (const bf16*)d_in[4], *w3 = (const bf16*)d_in[5], *w2 = (const bf16*)d_in[6];
  const bf16 *c = (const bf16*)d_in[7], *wm = (const bf16*)d_in[8];
  void* fn = nullptr;
  cudaDriverEntryPointQueryResult qr;
  cudaGetDriverEntryPoint("cuTensorMapEncodeTiled", &fn, cudaEnableDefault, &qr);
  EncodeFn enc = (EncodeFn)fn;
  CUtensorMap m_qkv, m_o, m_1, m_3, m_2;
  {
    const cuuint64_t rs = 3 * D_ * 2, dims[5] = {3 * D_, 2, 4, 4, 16}, st[4] = {rs, 8 * rs, 2 * rs, 32 * rs};
    const cuuint32_t box[5] = {64, 2, 4, 4, 2};
    make_map(enc, &m_qkv, wqkv, 5, dims, st, box);
  }
  make_map2(enc, &m_o, wo, D_, D_);
  make_map2(enc, &m_1, w1, F_, D_);
  make_map2(enc, &m_3, w3, F_, D_);
  make_map2(enc, &m_2, w2, D_, F_);
  cudaFuncSetAttribute(k_qkv, cudaFuncAttributeMaxDynamicSharedMemorySize, QKV_SMEM);
  cudaFuncSetAttribute(k_attn, cudaFuncAttributeMaxDynamicSharedMemorySize, ATT_SMEM);
  cudaFuncSetAttribute(k_ffn, cudaFuncAttributeMaxDynamicSharedMemorySize, FFN_SMEM);
  launch(k_mod, 96, 256, 0, false, c, wm);
  launch(k_qkv, 128, 256, QKV_SMEM, true, m_qkv, x);
  launch(k_attn, 128, ATT_THREADS, ATT_SMEM, true, wo, w1, w3, w2);
  launch(k_ffn, 128, 384, FFN_SMEM, true, m_o, m_1, m_3, m_2, x, (bf16*)d_out);
}
```

```cpp
#include <cuda_runtime.h>
#include <cuda_bf16.h>
#include <cuda_fp16.h>
#include <cuda.h>
#include <stdint.h>

typedef __nv_bfloat16 bf16;
constexpr int S_ = 2048, D_ = 512, F_ = 1376, NH = 32;
constexpr int KS_F = F_ / 16;

__device__ __align__(16) bf16 g_mod[6 * D_];
__device__ uint4 g_q[NH * 2 * S_];
__device__ uint4 g_k[NH * 2 * S_];
__device__ uint4 g_v[NH * 2 * S_];
__device__ uint4 g_attn[128 * 32 * 32];
__device__ uint4 g_x1[128 * 32 * 32];
__device__ uint4 g_act[128 * KS_F * 32];
__device__ unsigned g_flags[2 * 128 * 8];

__device__ __forceinline__ uint32_t smem_u32(const void* p) { return (uint32_t)__cvta_generic_to_shared(p); }
__device__ __forceinline__ void mbar_init(uint32_t b, uint32_t n) { asm volatile("mbarrier.init.shared::cta.b64 [%0], %1;" ::"r"(b), "r"(n) : "memory"); }
__device__ __forceinline__ void mbar_expect(uint32_t b, uint32_t bytes) { asm volatile("mbarrier.arrive.expect_tx.shared::cta.b64 _, [%0], %1;" ::"r"(b), "r"(bytes) : "memory"); }
__device__ __forceinline__ void mbar_arrive(uint32_t b) { asm volatile("mbarrier.arrive.shared::cta.b64 _, [%0];" ::"r"(b) : "memory"); }
__device__ __forceinline__ void mbar_wait(uint32_t b, uint32_t ph) {
  asm volatile("{.reg .pred p; .reg .u32 n; mov.u32 n, 0;\n"
               "W: mbarrier.try_wait.parity.shared::cta.b64 p, [%0], %1;\n"
               "@p bra D; add.u32 n, n, 1; setp.lt.u32 p, n, 0x4000000; @p bra W;\n"
               "D: }" ::"r"(b), "r"(ph) : "memory");
}
__device__ __forceinline__ void mbar_wait_cluster(uint32_t b, uint32_t ph) {
  asm volatile("{.reg .pred p; .reg .u32 n; mov.u32 n, 0;\n"
               "W: mbarrier.try_wait.parity.acquire.cluster.shared::cta.b64 p, [%0], %1;\n"
               "@p bra D; add.u32 n, n, 1; setp.lt.u32 p, n, 0x4000000; @p bra W;\n"
               "D: }" ::"r"(b), "r"(ph) : "memory");
}
__device__ __forceinline__ void tma2d(uint32_t dst, const CUtensorMap* m, int c0, int c1, uint32_t bar) {
  asm volatile("cp.async.bulk.tensor.2d.shared::cluster.global.mbarrier::complete_tx::bytes [%0], [%1, {%3, %4}], [%2];"
               ::"r"(dst), "l"(m), "r"(bar), "r"(c0), "r"(c1) : "memory");
}
__device__ __forceinline__ void tma5d(uint32_t dst, const CUtensorMap* m, int c0, int c4, uint32_t bar) {
  asm volatile("cp.async.bulk.tensor.5d.shared::cluster.global.mbarrier::complete_tx::bytes [%0], [%1, {%3, 0, 0, 0, %4}], [%2];"
               ::"r"(dst), "l"(m), "r"(bar), "r"(c0), "r"(c4) : "memory");
}
__device__ __forceinline__ void bulk_g2s(uint32_t dst, const void* src, uint32_t bytes, uint32_t bar) {
  asm volatile("cp.async.bulk.shared::cluster.global.mbarrier::complete_tx::bytes [%0], [%1], %2, [%3];"
               ::"r"(dst), "l"(src), "r"(bytes), "r"(bar) : "memory");
}
__device__ __forceinline__ void l2_prefetch(const void* src, uint32_t bytes) {
  asm volatile("cp.async.bulk.prefetch.L2.global [%0], %1;" ::"l"(src), "r"(bytes) : "memory");
}
__device__ __forceinline__ void pdl_wait() { asm volatile("griddepcontrol.wait;" ::: "memory"); }
__device__ __forceinline__ void pdl_trigger() { asm volatile("griddepcontrol.launch_dependents;" ::: "memory"); }
__device__ __forceinline__ void wg_fence() { asm volatile("wgmma.fence.sync.aligned;" ::: "memory"); }
__device__ __forceinline__ void wg_commit() { asm volatile("wgmma.commit_group.sync.aligned;" ::: "memory"); }
template <int N> __device__ __forceinline__ void wg_wait() { asm volatile("wgmma.wait_group.sync.aligned %0;" ::"n"(N) : "memory"); }
template <int N> __device__ __forceinline__ void reg_fence(float* r) {
#pragma unroll
  for (int i = 0; i < N; i++) asm volatile("" : "+f"(r[i])::"memory");
}
template <int N> __device__ __forceinline__ void reg_fence(uint32_t* r) {
#pragma unroll
  for (int i = 0; i < N; i++) asm volatile("" : "+r"(r[i])::"memory");
}
__device__ __forceinline__ uint4 ldg128(const void* p) {
  uint4 v; asm volatile("ld.global.L1::no_allocate.v4.u32 {%0,%1,%2,%3}, [%4];" : "=r"(v.x), "=r"(v.y), "=r"(v.z), "=r"(v.w) : "l"(p) : "memory"); return v;
}
__device__ __forceinline__ uint4 ldg128_nc(const void* p) {
  uint4 v; asm volatile("ld.global.nc.L1::no_allocate.v4.u32 {%0,%1,%2,%3}, [%4];" : "=r"(v.x), "=r"(v.y), "=r"(v.z), "=r"(v.w) : "l"(p)); return v;
}
__device__ __forceinline__ uint32_t pack_bf16(float lo, float hi) { uint32_t r; asm("cvt.rn.bf16x2.f32 %0, %1, %2;" : "=r"(r) : "f"(hi), "f"(lo)); return r; }
__device__ __forceinline__ uint32_t pack_f16(float lo, float hi) { uint32_t r; asm("cvt.rn.satfinite.f16x2.f32 %0, %1, %2;" : "=r"(r) : "f"(hi), "f"(lo)); return r; }
__device__ __forceinline__ float bf_lo(uint32_t v) { return __uint_as_float(v << 16); }
__device__ __forceinline__ float bf_hi(uint32_t v) { return __uint_as_float(v & 0xffff0000u); }
__device__ __forceinline__ uint32_t bf_fma2(uint32_t a, uint32_t b, uint32_t c) { uint32_t r; asm("fma.rn.bf16x2 %0, %1, %2, %3;" : "=r"(r) : "r"(a), "r"(b), "r"(c)); return r; }
__device__ __forceinline__ float ex2f(float x) { float r; asm("ex2.approx.ftz.f32 %0, %1;" : "=f"(r) : "f"(x)); return r; }
__device__ __forceinline__ float rcpf(float x) { float r; asm("rcp.approx.ftz.f32 %0, %1;" : "=f"(r) : "f"(x)); return r; }
__device__ __forceinline__ uint32_t desc_lo(uint32_t addr, uint32_t lbo) { return ((addr & 0x3FFFF) >> 4) | ((lbo >> 4) << 16); }
#define MMA(fn, off, accum, d, a, dlo) fn(d, a, dlo, off, accum)
__device__ __forceinline__ uint64_t desc_plain(uint32_t addr, uint32_t lbo, uint32_t sbo) {
  return (uint64_t)((addr & 0x3FFFF) >> 4) | ((uint64_t)(lbo >> 4) << 16) | ((uint64_t)(sbo >> 4) << 32);
}
#define NPOLY 9
__host__ __device__ constexpr bool poly_grp(int j) { return ((j & 15) * NPOLY) / 16 != (((j & 15) + 1) * NPOLY) / 16; }
#define TS(k, s, cond)
__device__ __forceinline__ void mma_qk64(uint32_t* d, uint64_t ac, uint64_t bc, uint64_t aq, uint64_t bk) {
  asm volatile("wgmma.mma_async.sync.aligned.m64n64k16.f16.f16.f16 {%0,%1,%2,%3,%4,%5,%6,%7,%8,%9,%10,%11,%12,%13,%14,%15}, %16, %17, 0, 1, 1, 0, 0;\n"
    "wgmma.mma_async.sync.aligned.m64n64k16.f16.f16.f16 {%0,%1,%2,%3,%4,%5,%6,%7,%8,%9,%10,%11,%12,%13,%14,%15}, %18, %19, 1, 1, 1, 0, 0;"
    : "=&r"(d[0]),"=&r"(d[1]),"=&r"(d[2]),"=&r"(d[3]),"=&r"(d[4]),"=&r"(d[5]),"=&r"(d[6]),"=&r"(d[7]),"=&r"(d[8]),"=&r"(d[9]),"=&r"(d[10]),"=&r"(d[11]),"=&r"(d[12]),"=&r"(d[13]),"=&r"(d[14]),"=&r"(d[15])
    : "l"(ac), "l"(bc), "l"(aq), "l"(bk));
}
__device__ __forceinline__ void mma_pv(float* d, const uint32_t* a, uint64_t desc) {
  asm volatile("wgmma.mma_async.sync.aligned.m64n24k16.f32.f16.f16 {%0,%1,%2,%3,%4,%5,%6,%7,%8,%9,%10,%11}, {%12,%13,%14,%15}, %16, 1, 1, 1, 1;"
    : "+f"(d[0]),"+f"(d[1]),"+f"(d[2]),"+f"(d[3]),"+f"(d[4]),"+f"(d[5]),"+f"(d[6]),"+f"(d[7]),"+f"(d[8]),"+f"(d[9]),"+f"(d[10]),"+f"(d[11])
    : "r"(a[0]), "r"(a[1]), "r"(a[2]), "r"(a[3]), "l"(desc));
}
__device__ __forceinline__ void mma_n64(float* d, const uint32_t* a, uint32_t dlo, int off, int acc) {
  asm volatile("{.reg .pred p; .reg .b32 t; .reg .b64 ds; add.u32 t, %36, %37; mov.b64 ds, {t, 0x40000040}; setp.ne.b32 p, %38, 0;\n"
    "wgmma.mma_async.sync.aligned.m64n64k16.f32.bf16.bf16 {%0,%1,%2,%3,%4,%5,%6,%7,%8,%9,%10,%11,%12,%13,%14,%15,%16,%17,%18,%19,%20,%21,%22,%23,%24,%25,%26,%27,%28,%29,%30,%31}, "
    "{%32,%33,%34,%35}, ds, p, 1, 1, 1;}"
    : "+f"(d[0]),"+f"(d[1]),"+f"(d[2]),"+f"(d[3]),"+f"(d[4]),"+f"(d[5]),"+f"(d[6]),"+f"(d[7]),"+f"(d[8]),"+f"(d[9]),"+f"(d[10]),"+f"(d[11]),"+f"(d[12]),"+f"(d[13]),"+f"(d[14]),"+f"(d[15]),"+f"(d[16]),"+f"(d[17]),"+f"(d[18]),"+f"(d[19]),"+f"(d[20]),"+f"(d[21]),"+f"(d[22]),"+f"(d[23]),"+f"(d[24]),"+f"(d[25]),"+f"(d[26]),"+f"(d[27]),"+f"(d[28]),"+f"(d[29]),"+f"(d[30]),"+f"(d[31])
    : "r"(a[0]), "r"(a[1]), "r"(a[2]), "r"(a[3]), "r"(dlo), "r"(off >> 4), "r"(acc));
}
__device__ __forceinline__ void mma_n128(float* d, const uint32_t* a, uint32_t dlo, int off, int acc) {
  asm volatile("{.reg .pred p; .reg .b32 t; .reg .b64 ds; add.u32 t, %68, %69; mov.b64 ds, {t, 0x40000040}; setp.ne.b32 p, %70, 0;\n"
    "wgmma.mma_async.sync.aligned.m64n128k16.f32.bf16.bf16 {%0,%1,%2,%3,%4,%5,%6,%7,%8,%9,%10,%11,%12,%13,%14,%15,%16,%17,%18,%19,%20,%21,%22,%23,%24,%25,%26,%27,%28,%29,%30,%31,%32,%33,%34,%35,%36,%37,%38,%39,%40,%41,%42,%43,%44,%45,%46,%47,%48,%49,%50,%51,%52,%53,%54,%55,%56,%57,%58,%59,%60,%61,%62,%63}, "
    "{%64,%65,%66,%67}, ds, p, 1, 1, 1;}"
    : "+f"(d[0]),"+f"(d[1]),"+f"(d[2]),"+f"(d[3]),"+f"(d[4]),"+f"(d[5]),"+f"(d[6]),"+f"(d[7]),"+f"(d[8]),"+f"(d[9]),"+f"(d[10]),"+f"(d[11]),"+f"(d[12]),"+f"(d[13]),"+f"(d[14]),"+f"(d[15]),"+f"(d[16]),"+f"(d[17]),"+f"(d[18]),"+f"(d[19]),"+f"(d[20]),"+f"(d[21]),"+f"(d[22]),"+f"(d[23]),"+f"(d[24]),"+f"(d[25]),"+f"(d[26]),"+f"(d[27]),"+f"(d[28]),"+f"(d[29]),"+f"(d[30]),"+f"(d[31]),"+f"(d[32]),"+f"(d[33]),"+f"(d[34]),"+f"(d[35]),"+f"(d[36]),"+f"(d[37]),"+f"(d[38]),"+f"(d[39]),"+f"(d[40]),"+f"(d[41]),"+f"(d[42]),"+f"(d[43]),"+f"(d[44]),"+f"(d[45]),"+f"(d[46]),"+f"(d[47]),"+f"(d[48]),"+f"(d[49]),"+f"(d[50]),"+f"(d[51]),"+f"(d[52]),"+f"(d[53]),"+f"(d[54]),"+f"(d[55]),"+f"(d[56]),"+f"(d[57]),"+f"(d[58]),"+f"(d[59]),"+f"(d[60]),"+f"(d[61]),"+f"(d[62]),"+f"(d[63])
    : "r"(a[0]), "r"(a[1]), "r"(a[2]), "r"(a[3]), "r"(dlo), "r"(off >> 4), "r"(acc));
}
__device__ __forceinline__ void mma_n48(float* d, const uint32_t* a, uint32_t dlo, int off, int acc) {
  asm volatile("{.reg .pred p; .reg .b32 t; .reg .b64 ds; add.u32 t, %28, %29; mov.b64 ds, {t, 0x40000040}; setp.ne.b32 p, %30, 0;\n"
    "wgmma.mma_async.sync.aligned.m64n48k16.f32.bf16.bf16 {%0,%1,%2,%3,%4,%5,%6,%7,%8,%9,%10,%11,%12,%13,%14,%15,%16,%17,%18,%19,%20,%21,%22,%23}, "
    "{%24,%25,%26,%27}, ds, p, 1, 1, 1;}"
    : "+f"(d[0]),"+f"(d[1]),"+f"(d[2]),"+f"(d[3]),"+f"(d[4]),"+f"(d[5]),"+f"(d[6]),"+f"(d[7]),"+f"(d[8]),"+f"(d[9]),"+f"(d[10]),"+f"(d[11]),"+f"(d[12]),"+f"(d[13]),"+f"(d[14]),"+f"(d[15]),"+f"(d[16]),"+f"(d[17]),"+f"(d[18]),"+f"(d[19]),"+f"(d[20]),"+f"(d[21]),"+f"(d[22]),"+f"(d[23])
    : "r"(a[0]), "r"(a[1]), "r"(a[2]), "r"(a[3]), "r"(dlo), "r"(off >> 4), "r"(acc));
}

__global__ void __launch_bounds__(256) k_mod(const bf16* __restrict__ c, const bf16* __restrict__ wm) {
  TS(0, 0, threadIdx.x == 0);
  pdl_trigger();
  __shared__ float red[8][32];
  const int tid = threadIdx.x, r = tid >> 2, cc = tid & 3, lane = tid & 31, w = tid >> 5;
  uint4 v[8];
#pragma unroll
  for (int i = 0; i < 8; i++) v[i] = ldg128_nc(wm + (size_t)(r + 64 * i) * (6 * D_) + blockIdx.x * 32 + cc * 8);
  if (blockIdx.x < 8) g_flags[blockIdx.x * 256 + tid] = 0;
  float acc[8];
#pragma unroll
  for (int e = 0; e < 8; e++) acc[e] = 0.f;
#pragma unroll
  for (int i = 0; i < 8; i++) {
    float cv = __bfloat162float(c[r + 64 * i]);
    float s = __bfloat162float(__float2bfloat16(cv / (1.f + __expf(-cv))));
    uint32_t u[4] = {v[i].x, v[i].y, v[i].z, v[i].w};
#pragma unroll
    for (int e = 0; e < 4; e++) { acc[2 * e] += s * bf_lo(u[e]); acc[2 * e + 1] += s * bf_hi(u[e]); }
  }
#pragma unroll
  for (int e = 0; e < 8; e++) {
    acc[e] += __shfl_xor_sync(~0u, acc[e], 4);
    acc[e] += __shfl_xor_sync(~0u, acc[e], 8);
    acc[e] += __shfl_xor_sync(~0u, acc[e], 16);
  }
  if (lane < 4) {
#pragma unroll
    for (int e = 0; e < 8; e++) red[w][lane * 8 + e] = acc[e];
  }
  __syncthreads();
  if (tid < 32) {
    float s = 0.f;
#pragma unroll
    for (int i = 0; i < 8; i++) s += red[i][tid];
    const int col = blockIdx.x * 32 + tid, seg = col >> 9;
    bf16 m = __float2bfloat16(s);
    if (seg == 1 || seg == 4) m = __float2bfloat16(1.f + __bfloat162float(m));
    g_mod[col] = m;
  }
  TS(0, 1, tid == 0);
}

constexpr int QKV_SMEM = 24 * 8192 + 2048 + 256 + 1024;
__global__ void __launch_bounds__(256, 1) k_qkv(const __grid_constant__ CUtensorMap tm_w, const bf16* __restrict__ x) {
  extern __shared__ __align__(1024) uint8_t sp[];
  const uint32_t sb = smem_u32(sp), dlo = desc_lo(sb, 8192);
  const uint32_t bars = sb + 24 * 8192 + 2048;
  const int tid = threadIdx.x, lane = tid & 31, w = tid >> 5, g = lane >> 2, q = lane & 3;
  const int nt = blockIdx.x & 7, rb16 = (blockIdx.x >> 3) * 8 + w;
  TS(1, 0, tid == 0);
  pdl_trigger();
  if (tid == 0) {
    for (int i = 0; i < 6; i++) mbar_init(bars + 8 * i, 1);
    asm volatile("fence.mbarrier_init.release.cluster;" ::: "memory");
    for (int i = 0; i < 6; i++) {
      mbar_expect(bars + 8 * i, 4 * 8192);
      for (int kb = 0; kb < 4; kb++)
        tma5d(sb + (i * 4 + kb) * 8192, &tm_w, nt * 192 + (i >> 1) * 64, ((i & 1) * 4 + kb) * 2, bars + 8 * i);
    }
  }
  uint32_t a[128];
  {
    const bf16* x0 = x + (size_t)(rb16 * 16 + g) * D_ + q * 8;
#pragma unroll
    for (int b = 0; b < 16; b++) {
      uint4 u = ldg128_nc(x0 + b * 32), v = ldg128_nc(x0 + 8 * D_ + b * 32);
      a[8 * b] = u.x; a[8 * b + 2] = u.y; a[8 * b + 4] = u.z; a[8 * b + 6] = u.w;
      a[8 * b + 1] = v.x; a[8 * b + 3] = v.y; a[8 * b + 5] = v.z; a[8 * b + 7] = v.w;
    }
    TS(1, 1, tid == 0 && a[127] != 0x12345);
    float s[4] = {0.f, 0.f, 0.f, 0.f};
#pragma unroll
    for (int i = 0; i < 128; i++) { s[i & 1] += bf_lo(a[i]); s[2 + (i & 1)] += bf_hi(a[i]); }
    float m0 = s[0] + s[2], m1 = s[1] + s[3];
    m0 += __shfl_xor_sync(~0u, m0, 1); m1 += __shfl_xor_sync(~0u, m1, 1);
    m0 += __shfl_xor_sync(~0u, m0, 2); m1 += __shfl_xor_sync(~0u, m1, 2);
    m0 *= -1.f / D_; m1 *= -1.f / D_;
    const uint32_t one = 0x3F803F80u, nm0 = pack_bf16(m0, m0), nm1 = pack_bf16(m1, m1);
    s[0] = s[1] = s[2] = s[3] = 0.f;
#pragma unroll
    for (int i = 0; i < 128; i++) {
      a[i] = bf_fma2(a[i], one, (i & 1) ? nm1 : nm0);
      float lo = bf_lo(a[i]), hi = bf_hi(a[i]);
      s[i & 1] += lo * lo; s[2 + (i & 1)] += hi * hi;
    }
    float v0 = s[0] + s[2], v1 = s[1] + s[3];
    v0 += __shfl_xor_sync(~0u, v0, 1); v1 += __shfl_xor_sync(~0u, v1, 1);
    v0 += __shfl_xor_sync(~0u, v0, 2); v1 += __shfl_xor_sync(~0u, v1, 2);
    v0 = rsqrtf(v0 * (1.f / D_) + 1e-5f); v1 = rsqrtf(v1 * (1.f / D_) + 1e-5f);
    const uint32_t r0 = pack_bf16(v0, v0), r1 = pack_bf16(v1, v1);
#pragma unroll
    for (int i = 0; i < 128; i++) a[i] = bf_fma2(a[i], (i & 1) ? r1 : r0, 0x80008000u);
  }
  TS(1, 2, tid == 0 && a[127] != 0x12345);
  pdl_wait();
  TS(1, 3, tid == 0);
  if (tid < 128) *(uint4*)(sp + 24 * 8192 + tid * 16) = ldg128((const uint8_t*)g_mod + tid * 16);
  __syncthreads();
  TS(1, 4, tid == 0);
  float acc[2][32];
#pragma unroll
  for (int kb = 0; kb < 8; kb++) {
#pragma unroll
    for (int b = 2 * kb; b < 2 * kb + 2; b++) {
      uint4 sa = *(const uint4*)(sp + 24 * 8192 + b * 64 + q * 16), ca = *(const uint4*)(sp + 24 * 8192 + 1024 + b * 64 + q * 16);
      uint32_t su[4] = {sa.x, sa.y, sa.z, sa.w}, cu[4] = {ca.x, ca.y, ca.z, ca.w};
#pragma unroll
      for (int j = 0; j < 8; j++) a[8 * b + j] = bf_fma2(a[8 * b + j], cu[j >> 1], su[j >> 1]);
    }
    if ((kb & 3) == 0) mbar_wait(bars + 8 * (kb >> 2), 0);
    wg_fence();
#pragma unroll
    for (int ks = 0; ks < 4; ks++) MMA(mma_n64, kb * 8192 + ks * 2048, kb | ks, acc[0], a + (kb * 4 + ks) * 4, dlo);
  }
  wg_commit();
#pragma unroll
  for (int p = 0; p < 3; p++) {
    if (p < 2) {
      mbar_wait(bars + 8 * (2 * p + 2), 0);
      mbar_wait(bars + 8 * (2 * p + 3), 0);
      wg_fence();
#pragma unroll
      for (int ks = 0; ks < 32; ks++) MMA(mma_n64, (p + 1) * 65536 + ks * 2048, ks, acc[(p + 1) & 1], a + ks * 4, dlo);
      wg_commit();
      wg_wait<1>();
    } else {
      wg_wait<0>();
    }
    float* d = acc[p & 1];
    reg_fence<32>(d);
    TS(1, 5 + p, tid == 0);
    const int col = nt * 192 + p * 64, sec = col >> 9, h0 = (col & 511) >> 4;
    {
      uint32_t* dst = (uint32_t*)(sec == 0 ? g_q : sec == 1 ? g_k : g_v) + (size_t)(h0 * 2 * S_ + rb16 * 16) * 4 + lane;
      const float sc = sec ? 1.f : 0.25f * 1.4426950408889634f;
      const float k0 = (sec == 1 && poly_grp(2 * rb16)) ? 1.f / 512 : sc, k1 = (sec == 1 && poly_grp(2 * rb16 + 1)) ? 1.f / 512 : sc;
#pragma unroll
      for (int jj = 0; jj < 8; jj++) {
        dst[jj * S_ * 4] = pack_f16(d[4 * jj] * k0, d[4 * jj + 1] * k0);
        dst[jj * S_ * 4 + 32] = pack_f16(d[4 * jj + 2] * k1, d[4 * jj + 3] * k1);
      }
    }
  }
  TS(1, 8, tid == 0);
}

__device__ __forceinline__ uint32_t h_max(uint32_t a, uint32_t b) { uint32_t r; asm("max.f16x2 %0, %1, %2;" : "=r"(r) : "r"(a), "r"(b)); return r; }
__device__ __forceinline__ uint32_t h_add(uint32_t a, uint32_t b) { uint32_t r; asm("add.rn.f16x2 %0, %1, %2;" : "=r"(r) : "r"(a), "r"(b)); return r; }
__device__ __forceinline__ uint32_t h_sub(uint32_t a, uint32_t b) { uint32_t r; asm("sub.rn.f16x2 %0, %1, %2;" : "=r"(r) : "r"(a), "r"(b)); return r; }
__device__ __forceinline__ uint32_t h_mul(uint32_t a, uint32_t b) { uint32_t r; asm("mul.rn.f16x2 %0, %1, %2;" : "=r"(r) : "r"(a), "r"(b)); return r; }
__device__ __forceinline__ uint32_t h_fma(uint32_t a, uint32_t b, uint32_t c) { uint32_t r; asm("fma.rn.f16x2 %0, %1, %2, %3;" : "=r"(r) : "r"(a), "r"(b), "r"(c)); return r; }
__device__ __forceinline__ uint32_t h_fma_relu(uint32_t a, uint32_t b, uint32_t c) { uint32_t r; asm("fma.rn.relu.f16x2 %0, %1, %2, %3;" : "=r"(r) : "r"(a), "r"(b), "r"(c)); return r; }
__device__ __forceinline__ uint32_t h_ex2(uint32_t a) { uint32_t r; asm("ex2.approx.f16x2 %0, %1;" : "=r"(r) : "r"(a)); return r; }
__device__ __forceinline__ float h_lo(uint32_t v) { return __half2float(__ushort_as_half((unsigned short)(v & 0xffff))); }
__device__ __forceinline__ float h_hi(uint32_t v) { return __half2float(__ushort_as_half((unsigned short)(v >> 16))); }

__device__ __forceinline__ uint32_t exp2_fma(uint32_t u) {
  const uint32_t n = h_fma_relu(u, 0x02000200u, 0u);
  const uint32_t f = h_fma(n, 0xF800F800u, u);
  uint32_t p = h_fma(f, 0x630D630Du, 0x47C047C0u);
  p = h_fma(p, f, 0x298C298Cu);
  p = h_fma_relu(p, f, 0x08000800u);
  return p + __funnelshift_l(n, n, 10);
}

#define PRE 1
#define TOP 5
__device__ __forceinline__ bool h_gt(uint32_t a, uint32_t b) {
  uint32_t r; asm("{.reg .pred p, q; setp.gt.f16x2 p|q, %1, %2; or.pred p, p, q; selp.u32 %0, 1, 0, p;}" : "=r"(r) : "r"(a), "r"(b)); return r;
}
__device__ __forceinline__ uint32_t row_max(const uint32_t* mx, uint32_t bias) {
  const uint32_t m0 = h_max(mx[0], h_fma(mx[2], 0x60006000u, bias)), m1 = h_max(mx[1], h_fma(mx[3], 0x60006000u, bias));
  uint32_t M = h_max(__byte_perm(m0, m1, 0x5410), __byte_perm(m0, m1, 0x7632));
  M = h_max(M, __shfl_xor_sync(~0u, M, 1));
  return h_max(M, __shfl_xor_sync(~0u, M, 2));
}
constexpr int NS = 16;
template <int J0> __device__ __forceinline__ bool block_over(const uint32_t* s) {
  uint32_t mx[2], pend[2]; int st[2] = {0, 0};
#pragma unroll
  for (int i = 0; i < NS; i++) {
    const int k = poly_grp(J0 + (i >> 1));
    if (st[k] == 0) { mx[k] = s[i]; st[k] = 1; }
    else if (st[k] == 1) { pend[k] = s[i]; st[k] = 2; }
    else { mx[k] = h_max(h_max(mx[k], pend[k]), s[i]); st[k] = 1; }
  }
  return h_gt(h_max(h_max(mx[0], pend[0]), h_fma(h_max(mx[1], pend[1]), 0x60006000u, 0xCA80CA80u)), 0x4BF04BF0u);
}
template <int J0> __device__ __forceinline__ void block_max(const uint32_t* s, uint32_t* mx) {
  uint32_t pend[4]; int st[4] = {0, 0, 0, 0};
#pragma unroll
  for (int i = 0; i < NS; i++) {
    const int k = (poly_grp(J0 + (i >> 1)) ? 2 : 0) + (i & 1);
    if (st[k] == 0) { mx[k] = s[i]; st[k] = 1; }
    else if (st[k] == 1) { pend[k] = s[i]; st[k] = 2; }
    else { mx[k] = h_max(h_max(mx[k], pend[k]), s[i]); st[k] = 1; }
  }
#pragma unroll
  for (int k = 0; k < 4; k++) if (st[k] == 2) mx[k] = h_max(mx[k], pend[k]);
}
__device__ __forceinline__ void set_offset(uint32_t c, uint32_t crow, bool q0) {
  if (q0) {
    asm volatile("st.shared.u32 [%0], %1;" ::"r"(crow), "r"(__byte_perm(c, 0x3C00u, 0x5410)) : "memory");
    asm volatile("st.shared.u32 [%0], %1;" ::"r"(crow + 128), "r"(__byte_perm(c, 0x3C00u, 0x5432)) : "memory");
  }
  asm volatile("fence.proxy.async.shared::cta;" ::: "memory");
  __syncwarp();
}
__device__ __forceinline__ void scores(uint32_t* s, uint64_t ac, uint64_t bc, uint64_t aq, uint64_t bk) {
  wg_fence();
  mma_qk64(s, ac, bc, aq, bk);
  wg_commit();
  wg_wait<0>();
  reg_fence<NS>(s);
}
template <int J0>
__device__ __forceinline__ void attn_step(float* o, uint32_t& c, uint32_t crow, bool q0, uint64_t ac, uint64_t bc, uint64_t aq,
                                          uint64_t dk, uint64_t dv) {
  uint32_t s[NS];
  scores(s, ac, bc + J0 * 8, aq, dk + J0 * 8);
  if (__any_sync(~0u, block_over<J0>(s))) {
    uint32_t mx[4];
    block_max<J0>(s, mx);
    const uint32_t up = h_max(h_sub(h_add(row_max(mx, 0xCA80CA80u), 0x66006600u - TOP * 0x10001u), 0x66006600u), 0u);
    const uint32_t cn = h_sub(c, up), dl = h_sub(cn, c), dp = h_mul(dl, 0x18001800u);
    c = cn;
    set_offset(c, crow, q0);
    const float a0 = ex2f(h_lo(dl)), a1 = ex2f(h_hi(dl));
    const uint32_t d0 = __byte_perm(dl, dl, 0x1010), d1 = __byte_perm(dl, dl, 0x3232);
    const uint32_t p0 = __byte_perm(dp, dp, 0x1010), p1 = __byte_perm(dp, dp, 0x3232);
    o[0] *= a0; o[1] *= a0; o[4] *= a0; o[5] *= a0; o[8] *= a0;
    o[2] *= a1; o[3] *= a1; o[6] *= a1; o[7] *= a1; o[10] *= a1;
#pragma unroll
    for (int i = 0; i < NS; i++) s[i] = h_add(s[i], poly_grp(J0 + (i >> 1)) ? ((i & 1) ? p1 : p0) : ((i & 1) ? d1 : d0));
  }
#pragma unroll
  for (int i = 0; i < NS; i++) s[i] = poly_grp(J0 + (i >> 1)) ? exp2_fma(s[i]) : h_ex2(s[i]);
  wg_fence();
#pragma unroll
  for (int ks = 0; ks < 4; ks++) mma_pv(o, s + ks * 4, dv + (J0 / 2 + ks) * 16);
  wg_commit();
  wg_wait<0>();
  reg_fence<12>(o);
}

constexpr int ATT_THREADS = 1024;
constexpr int A_Q = 5 * 32768, A_C = A_Q + 16384, A_B = A_C + 8192, A_BAR = A_B + 4096, ATT_SMEM = A_BAR + 128 + 1024;
__global__ void __launch_bounds__(ATT_THREADS, 1) k_attn(const bf16* __restrict__ wo, const bf16* __restrict__ w1,
                                                 const bf16* __restrict__ w3, const bf16* __restrict__ w2) {
  extern __shared__ __align__(1024) uint8_t sp[];
  const uint32_t sb = smem_u32(sp);
  const uint32_t bars = sb + A_BAR;
  const int tid = threadIdx.x, lane = tid & 31, w = tid >> 5;
  const int head = blockIdx.x >> 2, quarter = blockIdx.x & 3;
  TS(2, 0, tid == 0);
  if (tid == 0) {
    for (int i = 0; i < 8; i++) mbar_init(bars + 8 * i, 1);
    asm volatile("fence.mbarrier_init.release.cluster;" ::: "memory");
  }
#pragma unroll
  for (int i = 0; i < 2048 / ATT_THREADS; i++) *(uint4*)(sp + 4 * 32768 + (i * ATT_THREADS + tid) * 16) = make_uint4(0x3C003C00u, 0x3C003C00u, 0x3C003C00u, 0x3C003C00u);
  if (tid < 768) *(uint4*)(sp + A_C + tid * 16) = make_uint4((tid >> 7) != 4 ? 0u : poly_grp(tid >> 3) ? 0x26801800u : 0x00003C00u, 0, 0, 0);
  asm volatile("fence.proxy.async.shared::cta;" ::: "memory");
  __syncthreads();
  pdl_wait();
  TS(2, 1, tid == 0);
  if (tid == 0) {
    for (int i = 0; i < 8; i++) {
      mbar_expect(bars + 8 * i, i ? 16384 : 32768);
      if (i == 0) {
        bulk_g2s(sb + A_Q, g_q + (head * 2) * S_ + quarter * 512, 8192, bars);
        bulk_g2s(sb + A_Q + 8192, g_q + (head * 2 + 1) * S_ + quarter * 512, 8192, bars);
      }
      bulk_g2s(sb + i * 4096, g_k + (head * 2) * S_ + i * 256, 4096, bars + 8 * i);
      bulk_g2s(sb + 32768 + i * 4096, g_k + (head * 2 + 1) * S_ + i * 256, 4096, bars + 8 * i);
      bulk_g2s(sb + 65536 + i * 4096, g_v + (head * 2) * S_ + i * 256, 4096, bars + 8 * i);
      bulk_g2s(sb + 98304 + i * 4096, g_v + (head * 2 + 1) * S_ + i * 256, 4096, bars + 8 * i);
    }
  }
  pdl_trigger();
  if (tid == 64) {
    l2_prefetch((const uint8_t*)wo + blockIdx.x * 4096, 4096);
    l2_prefetch((const uint8_t*)w1 + blockIdx.x * 11008, 11008);
    l2_prefetch((const uint8_t*)w3 + blockIdx.x * 11008, 11008);
    l2_prefetch((const uint8_t*)w2 + blockIdx.x * 11008, 11008);
  }
  const int wg = __shfl_sync(~0u, w >> 2, 0);
  const uint64_t dk0 = desc_plain(sb, 32768, 128), dv0 = desc_plain(sb + 65536, 128, 32768);
  const uint64_t aq = desc_plain(sb + A_Q + wg * 1024, 8192, 128), ac = desc_plain(sb + A_C + wg * 1024, 0, 128);
  const uint64_t bc = desc_plain(sb + A_B, 2048, 128);
  const bool q0 = (lane & 3) == 0;
  const uint32_t crow = sb + A_C + w * 256 + (lane >> 2) * 16;
  float o[12];
#pragma unroll
  for (int i = 0; i < 12; i++) o[i] = 0.f;
  uint32_t c = 0xFBFFFBFFu;
  mbar_wait(bars, 0);
#pragma unroll 1
  for (int j = 0; j < PRE; j++) {
    uint32_t s[NS], mx[4];
    scores(s, ac, bc, aq, dk0 + j * 128);
    block_max<0>(s, mx);
    c = h_max(c, row_max(mx, 0u));
  }
  TS(2, 2, tid == 0);
  c = h_sub(h_sub(0x66006600u + TOP * 0x10001u, c), 0x66006600u);
  set_offset(c, crow, q0);
#pragma unroll 1
  for (int kb = 0; kb < S_; kb += 128) {
    if ((kb & 255) == 0) mbar_wait(bars + (kb >> 5), 0);
    attn_step<0>(o, c, crow, q0, ac, bc, aq, dk0 + kb, dv0 + kb);
    attn_step<8>(o, c, crow, q0, ac, bc, aq, dk0 + kb, dv0 + kb);
  }
  TS(2, 3, tid == 0);
  TS(2, 5, tid == 896);
  const float i0 = 1.f / o[8], i1 = 1.f / o[10];
  g_attn[((quarter * 32 + w) * 32 + head) * 32 + lane] = make_uint4(pack_bf16(o[0] * i0, o[1] * i0), pack_bf16(o[2] * i1, o[3] * i1),
                                                                    pack_bf16(o[4] * i0, o[5] * i0), pack_bf16(o[6] * i1, o[7] * i1));
}

__device__ float4 g_stats[128 * 16 * 4];
constexpr int NST = 13, STB = 16384;
constexpr int FFN_SMEM = NST * STB + 4096 + 512 + 1024;

__device__ __forceinline__ void flag_signal(unsigned* f, int lane) {
  __syncwarp();
  if (lane == 0) asm volatile("red.release.gpu.global.add.u32 [%0], 1;" ::"l"(f) : "memory");
}
__device__ __forceinline__ void flag_wait(const unsigned* f, int lane) {
  if (lane == 0) {
    unsigned v, n = 0;
    do {
      asm volatile("ld.acquire.gpu.global.u32 %0, [%1];" : "=r"(v) : "l"(f) : "memory");
      if (++n > (1u << 24)) __trap();
    } while (v < 8);
  }
  __syncwarp();
}
__device__ __forceinline__ float silu_mul(float g, float u) { return g * u * rcpf(1.f + ex2f(g * -1.4426950408889634f)); }

__global__ void __launch_bounds__(384, 1) __cluster_dims__(2, 1, 1)
k_ffn(const __grid_constant__ CUtensorMap tm_wo, const __grid_constant__ CUtensorMap tm_w1, const __grid_constant__ CUtensorMap tm_w3,
      const __grid_constant__ CUtensorMap tm_w2, const bf16* __restrict__ x, bf16* __restrict__ out) {
  extern __shared__ __align__(1024) uint8_t sp[];
  const uint32_t sb = smem_u32(sp), dlo = desc_lo(sb, 8192);
  const uint32_t bfull = sb + NST * STB + 4096, bempty = bfull + 8 * NST, bpeer = bempty + 8 * NST, bx = bpeer + 8;
  const int tid = threadIdx.x, lane = tid & 31, w = tid >> 5;
  const int j = blockIdx.x & 7, rb = blockIdx.x >> 3, kh = j & 1;
  TS(3, 0, tid == 0);
  if (tid == 0) {
    for (int i = 0; i < NST; i++) { mbar_init(bfull + 8 * i, 1); mbar_init(bempty + 8 * i, 8); }
    mbar_init(bpeer, 8);
    for (int i = 0; i < 8; i++) { mbar_init(bx + 8 * i, 1); }
    asm volatile("fence.mbarrier_init.release.cluster;" ::: "memory");
    for (int i = 0; i < 8; i++) mbar_expect(bx + 8 * i, 4096);
  }
  if (tid < 256) *(uint4*)(sp + NST * STB + tid * 16) = ldg128((const uint8_t*)g_mod + 2048 + tid * 16);
  __syncthreads();
  asm volatile("barrier.cluster.arrive.release.aligned;" ::: "memory");
  if (w >= 8) {
    asm volatile("setmaxnreg.dec.sync.aligned.u32 24;");
    if (tid == 256) {
      int slot = 0, ph = 1;
#pragma unroll 1
      for (int st = 0; st < 39; st++) {
        const CUtensorMap *m0, *m1; int x0, y0, x1, y1;
        if (st < 4) { m0 = m1 = &tm_wo; x0 = x1 = j * 64; y0 = st * 128; y1 = y0 + 64; }
        else if (st < 28) { m0 = &tm_w1; m1 = &tm_w3; x0 = x1 = j * 176 + ((st - 4) >> 3) * 64; y0 = y1 = ((st - 4) & 7) * 64; }
        else { m0 = m1 = &tm_w2; x0 = (j >> 1) * 128; x1 = x0 + 64; y0 = y1 = kh * 688 + (st - 28) * 64; }
        mbar_wait(bempty + 8 * slot, ph);
        mbar_expect(bfull + 8 * slot, STB);
        tma2d(sb + slot * STB, m0, x0, y0, bfull + 8 * slot);
        tma2d(sb + slot * STB + 8192, m1, x1, y1, bfull + 8 * slot);
        if (++slot == NST) { slot = 0; ph ^= 1; }
      }
    }
    __syncwarp();
    asm volatile("barrier.cluster.wait.acquire.aligned;" ::: "memory");
  } else {
    asm volatile("setmaxnreg.inc.sync.aligned.u32 240;");
    const int g = lane >> 2, q = lane & 3, rb16 = rb * 8 + w;
    const uint32_t* smod = (const uint32_t*)(sp + NST * STB);
    uint32_t a[128];
    float acc[64];
    uint32_t xr[16];
    {
      const uint32_t* x0 = (const uint32_t*)(x + (size_t)(rb16 * 16 + g) * D_ + j * 64) + q;
#pragma unroll
      for (int i = 0; i < 8; i++) { xr[2 * i] = __ldg(x0 + i * 4); xr[2 * i + 1] = __ldg(x0 + 8 * D_ / 2 + i * 4); }
    }
    asm volatile("barrier.cluster.wait.acquire.aligned;" ::: "memory");
    TS(3, 1, tid == 0);
    pdl_wait();
    TS(3, 2, tid == 0);
#pragma unroll
    for (int i = 0; i < 32; i++) { uint4 u = ldg128(g_attn + (rb16 * 32 + i) * 32 + lane); a[4 * i] = u.x; a[4 * i + 1] = u.y; a[4 * i + 2] = u.z; a[4 * i + 3] = u.w; }
#pragma unroll
    for (int st = 0; st < 4; st++) {
      mbar_wait(bfull + 8 * st, 0);
      wg_fence();
#pragma unroll
      for (int ks = 0; ks < 8; ks++) MMA(mma_n64, st * STB + ks * 2048, st | ks, acc, a + (st * 8 + ks) * 4, dlo);
    }
    wg_commit();
    wg_wait<0>();
    reg_fence<32>(acc);
    TS(3, 3, tid == 0);
    if (lane < 4) mbar_arrive(bempty + 8 * lane);
    {
      float s0 = 0.f, s1 = 0.f;
#pragma unroll
      for (int i = 0; i < 8; i++) {
        const uint32_t ga = smod[j * 32 + i * 4 + q];
        xr[2 * i] = pack_bf16(bf_lo(xr[2 * i]) + bf_lo(ga) * acc[4 * i], bf_hi(xr[2 * i]) + bf_hi(ga) * acc[4 * i + 1]);
        xr[2 * i + 1] = pack_bf16(bf_lo(xr[2 * i + 1]) + bf_lo(ga) * acc[4 * i + 2], bf_hi(xr[2 * i + 1]) + bf_hi(ga) * acc[4 * i + 3]);
        s0 += bf_lo(xr[2 * i]) + bf_hi(xr[2 * i]); s1 += bf_lo(xr[2 * i + 1]) + bf_hi(xr[2 * i + 1]);
      }
#pragma unroll
      for (int i = 0; i < 4; i++) g_x1[(rb16 * 32 + j * 4 + i) * 32 + lane] = make_uint4(xr[4 * i], xr[4 * i + 1], xr[4 * i + 2], xr[4 * i + 3]);
      s0 += __shfl_xor_sync(~0u, s0, 1); s1 += __shfl_xor_sync(~0u, s1, 1);
      s0 += __shfl_xor_sync(~0u, s0, 2); s1 += __shfl_xor_sync(~0u, s1, 2);
      s0 *= 1.f / 64; s1 *= 1.f / 64;
      float v0 = 0.f, v1 = 0.f;
#pragma unroll
      for (int i = 0; i < 8; i++) {
        float d = bf_lo(xr[2 * i]) - s0; v0 += d * d; d = bf_hi(xr[2 * i]) - s0; v0 += d * d;
        d = bf_lo(xr[2 * i + 1]) - s1; v1 += d * d; d = bf_hi(xr[2 * i + 1]) - s1; v1 += d * d;
      }
      v0 += __shfl_xor_sync(~0u, v0, 1); v1 += __shfl_xor_sync(~0u, v1, 1);
      v0 += __shfl_xor_sync(~0u, v0, 2); v1 += __shfl_xor_sync(~0u, v1, 2);
      if (q < 2) ((float2*)g_stats)[(rb16 * 16 + g + q * 8) * 8 + j] = q ? make_float2(s1, v1) : make_float2(s0, v0);
    }
    flag_signal(g_flags + rb16 * 8, lane);
    TS(3, 4, tid == 0);
    flag_wait(g_flags + rb16 * 8, lane);
    TS(3, 5, tid == 0);
    uint32_t r0, r1, n0, n1;
    {
      uint4 t0 = ldg128(g_stats + (rb16 * 16 + g) * 4 + q), t1 = ldg128(g_stats + (rb16 * 16 + g + 8) * 4 + q);
#pragma unroll
      for (int i = 0; i < 32; i++) { uint4 u = ldg128(g_x1 + (rb16 * 32 + i) * 32 + lane); a[4 * i] = u.x; a[4 * i + 1] = u.y; a[4 * i + 2] = u.z; a[4 * i + 3] = u.w; }
      float m0 = __uint_as_float(t0.x) + __uint_as_float(t0.z), m1 = __uint_as_float(t1.x) + __uint_as_float(t1.z);
      m0 += __shfl_xor_sync(~0u, m0, 1); m1 += __shfl_xor_sync(~0u, m1, 1);
      m0 += __shfl_xor_sync(~0u, m0, 2); m1 += __shfl_xor_sync(~0u, m1, 2);
      m0 *= 0.125f; m1 *= 0.125f;
      float d0 = __uint_as_float(t0.x) - m0, d1 = __uint_as_float(t0.z) - m0;
      float v0 = __uint_as_float(t0.y) + __uint_as_float(t0.w) + 64.f * (d0 * d0 + d1 * d1);
      d0 = __uint_as_float(t1.x) - m1; d1 = __uint_as_float(t1.z) - m1;
      float v1 = __uint_as_float(t1.y) + __uint_as_float(t1.w) + 64.f * (d0 * d0 + d1 * d1);
      v0 += __shfl_xor_sync(~0u, v0, 1); v1 += __shfl_xor_sync(~0u, v1, 1);
      v0 += __shfl_xor_sync(~0u, v0, 2); v1 += __shfl_xor_sync(~0u, v1, 2);
      v0 = rsqrtf(v0 * (1.f / D_) + 1e-5f); v1 = rsqrtf(v1 * (1.f / D_) + 1e-5f);
      r0 = pack_bf16(v0, v0); r1 = pack_bf16(v1, v1);
      m0 *= -bf_lo(r0); m1 *= -bf_lo(r1);
      n0 = pack_bf16(m0, m0); n1 = pack_bf16(m1, m1);
    }
#pragma unroll
    for (int p = 0; p < 3; p++) {
      float g48[24], u48[24];
#pragma unroll
      for (int kb = 0; kb < 8; kb++) {
        const int st = 4 + p * 8 + kb, slot = st % NST;
        if (p == 0) {
#pragma unroll
          for (int i = kb * 8; i < kb * 8 + 8; i++) {
            const uint32_t sv = smod[256 + i * 4 + q], cv = smod[512 + i * 4 + q];
            a[2 * i] = bf_fma2(bf_fma2(a[2 * i], r0, n0), cv, sv);
            a[2 * i + 1] = bf_fma2(bf_fma2(a[2 * i + 1], r1, n1), cv, sv);
          }
        }
        mbar_wait(bfull + 8 * slot, (st / NST) & 1);
        wg_fence();
#pragma unroll
        for (int ks = 0; ks < 4; ks++) {
          if (p < 2) MMA(mma_n128, slot * STB + ks * 2048, kb | ks, acc, a + (kb * 4 + ks) * 4, dlo);
          else {
            MMA(mma_n48, slot * STB + ks * 2048, kb | ks, g48, a + (kb * 4 + ks) * 4, dlo);
            MMA(mma_n48, slot * STB + 8192 + ks * 2048, kb | ks, u48, a + (kb * 4 + ks) * 4, dlo);
          }
        }
        wg_commit();
        if (kb > 0) { wg_wait<1>(); if (lane == 0) mbar_arrive(bempty + 8 * ((st - 1) % NST)); }
      }
      wg_wait<0>();
      if (p < 2) reg_fence<64>(acc); else { reg_fence<24>(g48); reg_fence<24>(u48); }
      TS(3, 6 + p, tid == 0);
      if (lane == 0) {
        mbar_arrive(bempty + 8 * ((4 + p * 8 + 7) % NST));
        if (p == 2) {
          uint32_t ra; asm volatile("mapa.shared::cluster.u32 %0, %1, %2;" : "=r"(ra) : "r"(bpeer), "r"(kh ^ 1));
          asm volatile("mbarrier.arrive.shared::cluster.b64 _, [%0];" ::"r"(ra) : "memory");
        }
      }
#pragma unroll
      for (int ks = 0; ks < (p < 2 ? 4 : 3); ks++) {
        const int kk = j * 11 + p * 4 + ks;
        const float* gt = (p < 2 ? acc : g48) + 8 * ks; const float* up = (p < 2 ? acc + 32 : u48) + 8 * ks;
        uint4 u = make_uint4(pack_bf16(silu_mul(gt[0], up[0]), silu_mul(gt[1], up[1])), pack_bf16(silu_mul(gt[2], up[2]), silu_mul(gt[3], up[3])),
                             pack_bf16(silu_mul(gt[4], up[4]), silu_mul(gt[5], up[5])), pack_bf16(silu_mul(gt[6], up[6]), silu_mul(gt[7], up[7])));
        if (kk < KS_F) g_act[(rb16 * KS_F + kk) * 32 + lane] = u;
      }
    }
    flag_signal(g_flags + 1024 + rb16 * 8, lane);
    TS(3, 9, tid == 0);
    flag_wait(g_flags + 1024 + rb16 * 8, lane);
    TS(3, 10, tid == 0);
    float acc3[64];
    const uint4* ap = g_act + (rb16 * KS_F + kh * 43) * 32 + lane;
#pragma unroll
    for (int i = 0; i < 32; i++) { uint4 u = ldg128(ap + i * 32); a[4 * i] = u.x; a[4 * i + 1] = u.y; a[4 * i + 2] = u.z; a[4 * i + 3] = u.w; }
#pragma unroll
    for (int kb = 0; kb < 11; kb++) {
      const int slot = (28 + kb) % NST;
      mbar_wait(bfull + 8 * slot, 0);
      wg_fence();
#pragma unroll
      for (int ks = 0; ks < (kb < 10 ? 4 : 3); ks++)
        MMA(mma_n128, slot * STB + ks * 2048, kb | ks, acc3, a + ((kb * 4 + ks) & 31) * 4, dlo);
      wg_commit();
      if (kb == 2) {
        wg_wait<0>();
        reg_fence<64>(acc3);
        TS(3, 11, tid == 0);
#pragma unroll
        for (int i = 0; i < 11; i++) { uint4 u = ldg128(ap + (32 + i) * 32); a[4 * i] = u.x; a[4 * i + 1] = u.y; a[4 * i + 2] = u.z; a[4 * i + 3] = u.w; }
      }
    }
#pragma unroll
    for (int i = 0; i < 4; i++) { uint4 u = ldg128(g_x1 + (rb16 * 32 + j * 4 + i) * 32 + lane); xr[4 * i] = u.x; xr[4 * i + 1] = u.y; xr[4 * i + 2] = u.z; xr[4 * i + 3] = u.w; }
    mbar_wait_cluster(bpeer, 0);
    wg_wait<0>();
    reg_fence<64>(acc3);
    TS(3, 12, tid == 0);
    {
      uint32_t ra, rbar;
      asm volatile("mapa.shared::cluster.u32 %0, %1, %2;" : "=r"(ra) : "r"(sb + tid * 16), "r"(kh ^ 1));
      asm volatile("mapa.shared::cluster.u32 %0, %1, %2;" : "=r"(rbar) : "r"(bx + 8 * w), "r"(kh ^ 1));
#pragma unroll
      for (int i = 0; i < 8; i++) {
        const float s0 = kh ? acc3[4 * i] : acc3[32 + 4 * i], s1 = kh ? acc3[4 * i + 1] : acc3[33 + 4 * i];
        const float s2 = kh ? acc3[4 * i + 2] : acc3[34 + 4 * i], s3 = kh ? acc3[4 * i + 3] : acc3[35 + 4 * i];
        asm volatile("st.async.weak.shared::cluster.mbarrier::complete_tx::bytes.v4.f32 [%0], {%1,%2,%3,%4}, [%5];"
                     ::"r"(ra + i * 4096), "f"(s0), "f"(s1), "f"(s2), "f"(s3), "r"(rbar) : "memory");
      }
    }
    mbar_wait_cluster(bx + 8 * w, 0);
    TS(3, 13, tid == 0);
    uint32_t* o0 = (uint32_t*)(out + (size_t)(rb16 * 16 + g) * D_ + j * 64) + q;
#pragma unroll
    for (int i = 0; i < 8; i++) {
      const float4 pv = *(const float4*)(sp + i * 4096 + tid * 16);
      const uint32_t gb = smod[768 + j * 32 + i * 4 + q];
      const float s0 = (kh ? acc3[32 + 4 * i] : acc3[4 * i]) + pv.x, s1 = (kh ? acc3[33 + 4 * i] : acc3[4 * i + 1]) + pv.y;
      const float s2 = (kh ? acc3[34 + 4 * i] : acc3[4 * i + 2]) + pv.z, s3 = (kh ? acc3[35 + 4 * i] : acc3[4 * i + 3]) + pv.w;
      o0[i * 4] = pack_bf16(bf_lo(xr[2 * i]) + bf_lo(gb) * s0, bf_hi(xr[2 * i]) + bf_hi(gb) * s1);
      o0[8 * D_ / 2 + i * 4] = pack_bf16(bf_lo(xr[2 * i + 1]) + bf_lo(gb) * s2, bf_hi(xr[2 * i + 1]) + bf_hi(gb) * s3);
    }
    TS(3, 14, tid == 0);
  }
}

typedef CUresult (*EncodeFn)(CUtensorMap*, CUtensorMapDataType, cuuint32_t, void*, const cuuint64_t*, const cuuint64_t*,
                             const cuuint32_t*, const cuuint32_t*, CUtensorMapInterleave, CUtensorMapSwizzle,
                             CUtensorMapL2promotion, CUtensorMapFloatOOBfill);
static void make_map(EncodeFn enc, CUtensorMap* m, const void* p, int rank, const cuuint64_t* dims, const cuuint64_t* strides, const cuuint32_t* box) {
  const cuuint32_t es[5] = {1, 1, 1, 1, 1};
  enc(m, CU_TENSOR_MAP_DATA_TYPE_BFLOAT16, rank, (void*)p, dims, strides, box, es, CU_TENSOR_MAP_INTERLEAVE_NONE,
      CU_TENSOR_MAP_SWIZZLE_128B, CU_TENSOR_MAP_L2_PROMOTION_L2_256B, CU_TENSOR_MAP_FLOAT_OOB_FILL_NONE);
}
static void make_map2(EncodeFn enc, CUtensorMap* m, const void* p, int cols, int rows) {
  const cuuint64_t dims[2] = {(cuuint64_t)cols, (cuuint64_t)rows}, st[1] = {(cuuint64_t)cols * 2};
  const cuuint32_t box[2] = {64, 64};
  make_map(enc, m, p, 2, dims, st, box);
}
template <typename... KA, typename... A>
static void launch(void (*k)(KA...), int grid, int block, int smem, bool pdl, A... args) {
  cudaLaunchConfig_t cfg = {};
  cfg.gridDim = dim3(grid); cfg.blockDim = dim3(block); cfg.dynamicSmemBytes = smem; cfg.stream = cudaStreamPerThread;
  cudaLaunchAttribute at[1];
  at[0].id = cudaLaunchAttributeProgrammaticStreamSerialization;
  at[0].val.programmaticStreamSerializationAllowed = 1;
  cfg.attrs = at; cfg.numAttrs = pdl ? 1 : 0;
  cudaLaunchKernelEx(&cfg, k, KA(args)...);
}

extern "C" void kernel_launch(void* const* d_in, const int* in_sizes, int n_in, void* d_out, int out_size) {
  const bf16 *x = (const bf16*)d_in[0], *wqkv = (const bf16*)d_in[1], *wo = (const bf16*)d_in[2];
  const bf16 *w1 = (const bf16*)d_in[4], *w3 = (const bf16*)d_in[5], *w2 = (const bf16*)d_in[6];
  const bf16 *c = (const bf16*)d_in[7], *wm = (const bf16*)d_in[8];
  void* fn = nullptr;
  cudaDriverEntryPointQueryResult qr;
  cudaGetDriverEntryPoint("cuTensorMapEncodeTiled", &fn, cudaEnableDefault, &qr);
  EncodeFn enc = (EncodeFn)fn;
  CUtensorMap m_qkv, m_o, m_1, m_3, m_2;
  {
    const cuuint64_t rs = 3 * D_ * 2, dims[5] = {3 * D_, 2, 4, 4, 16}, st[4] = {rs, 8 * rs, 2 * rs, 32 * rs};
    const cuuint32_t box[5] = {64, 2, 4, 4, 2};
    make_map(enc, &m_qkv, wqkv, 5, dims, st, box);
  }
  make_map2(enc, &m_o, wo, D_, D_);
  make_map2(enc, &m_1, w1, F_, D_);
  make_map2(enc, &m_3, w3, F_, D_);
  make_map2(enc, &m_2, w2, D_, F_);
  cudaFuncSetAttribute(k_qkv, cudaFuncAttributeMaxDynamicSharedMemorySize, QKV_SMEM);
  cudaFuncSetAttribute(k_attn, cudaFuncAttributeMaxDynamicSharedMemorySize, ATT_SMEM);
  cudaFuncSetAttribute(k_ffn, cudaFuncAttributeMaxDynamicSharedMemorySize, FFN_SMEM);
  launch(k_mod, 96, 256, 0, false, c, wm);
  launch(k_qkv, 128, 256, QKV_SMEM, true, m_qkv, x);
  launch(k_attn, 128, ATT_THREADS, ATT_SMEM, true, wo, w1, w3, w2);
  launch(k_ffn, 128, 384, FFN_SMEM, true, m_o, m_1, m_3, m_2, x, (bf16*)d_out);
}
```

```cpp
#include <cuda_runtime.h>
#include <cuda_bf16.h>
#include <cuda_fp16.h>
#include <cuda.h>
#include <stdint.h>

typedef __nv_bfloat16 bf16;
constexpr int S_ = 2048, D_ = 512, F_ = 1376, NH = 32;
constexpr int KS_F = F_ / 16;

__device__ __align__(16) bf16 g_mod[6 * D_];
__device__ uint4 g_q[NH * 2 * S_];
__device__ uint4 g_k[NH * 2 * S_];
__device__ uint4 g_v[NH * 2 * S_];
__device__ uint4 g_attn[128 * 32 * 32];
__device__ uint4 g_x1[128 * 32 * 32];
__device__ uint4 g_act[128 * KS_F * 32];
__device__ unsigned g_flags[2 * 128 * 8];

__device__ __forceinline__ uint32_t smem_u32(const void* p) { return (uint32_t)__cvta_generic_to_shared(p); }
__device__ __forceinline__ void mbar_init(uint32_t b, uint32_t n) { asm volatile("mbarrier.init.shared::cta.b64 [%0], %1;" ::"r"(b), "r"(n) : "memory"); }
__device__ __forceinline__ void mbar_expect(uint32_t b, uint32_t bytes) { asm volatile("mbarrier.arrive.expect_tx.shared::cta.b64 _, [%0], %1;" ::"r"(b), "r"(bytes) : "memory"); }
__device__ __forceinline__ void mbar_arrive(uint32_t b) { asm volatile("mbarrier.arrive.shared::cta.b64 _, [%0];" ::"r"(b) : "memory"); }
__device__ __forceinline__ void mbar_wait(uint32_t b, uint32_t ph) {
  asm volatile("{.reg .pred p; .reg .u32 n;\n"
               "mbarrier.try_wait.parity.shared::cta.b64 p, [%0], %1; @p bra D;\n"
               "mov.u32 n, 0;\n"
               "W: mbarrier.try_wait.parity.shared::cta.b64 p, [%0], %1;\n"
               "@p bra D; add.u32 n, n, 1; setp.lt.u32 p, n, 0x4000000; @p bra W;\n"
               "D: }" ::"r"(b), "r"(ph) : "memory");
}
__device__ __forceinline__ void mbar_wait_cluster(uint32_t b, uint32_t ph) {
  asm volatile("{.reg .pred p; .reg .u32 n; mov.u32 n, 0;\n"
               "W: mbarrier.try_wait.parity.acquire.cluster.shared::cta.b64 p, [%0], %1;\n"
               "@p bra D; add.u32 n, n, 1; setp.lt.u32 p, n, 0x4000000; @p bra W;\n"
               "D: }" ::"r"(b), "r"(ph) : "memory");
}
__device__ __forceinline__ void tma2d(uint32_t dst, const CUtensorMap* m, int c0, int c1, uint32_t bar) {
  asm volatile("cp.async.bulk.tensor.2d.shared::cluster.global.mbarrier::complete_tx::bytes [%0], [%1, {%3, %4}], [%2];"
               ::"r"(dst), "l"(m), "r"(bar), "r"(c0), "r"(c1) : "memory");
}
__device__ __forceinline__ void tma5d(uint32_t dst, const CUtensorMap* m, int c0, int c4, uint32_t bar) {
  asm volatile("cp.async.bulk.tensor.5d.shared::cluster.global.mbarrier::complete_tx::bytes [%0], [%1, {%3, 0, 0, 0, %4}], [%2];"
               ::"r"(dst), "l"(m), "r"(bar), "r"(c0), "r"(c4) : "memory");
}
__device__ __forceinline__ void bulk_g2s(uint32_t dst, const void* src, uint32_t bytes, uint32_t bar) {
  asm volatile("cp.async.bulk.shared::cluster.global.mbarrier::complete_tx::bytes [%0], [%1], %2, [%3];"
               ::"r"(dst), "l"(src), "r"(bytes), "r"(bar) : "memory");
}
__device__ __forceinline__ void l2_prefetch(const void* src, uint32_t bytes) {
  asm volatile("cp.async.bulk.prefetch.L2.global [%0], %1;" ::"l"(src), "r"(bytes) : "memory");
}
__device__ __forceinline__ void pdl_wait() { asm volatile("griddepcontrol.wait;" ::: "memory"); }
__device__ __forceinline__ void pdl_trigger() { asm volatile("griddepcontrol.launch_dependents;" ::: "memory"); }
__device__ __forceinline__ void wg_fence() { asm volatile("wgmma.fence.sync.aligned;" ::: "memory"); }
__device__ __forceinline__ void wg_commit() { asm volatile("wgmma.commit_group.sync.aligned;" ::: "memory"); }
template <int N> __device__ __forceinline__ void wg_wait() { asm volatile("wgmma.wait_group.sync.aligned %0;" ::"n"(N) : "memory"); }
template <int N> __device__ __forceinline__ void reg_fence(float* r) {
#pragma unroll
  for (int i = 0; i < N; i++) asm volatile("" : "+f"(r[i])::"memory");
}
template <int N> __device__ __forceinline__ void reg_fence(uint32_t* r) {
#pragma unroll
  for (int i = 0; i < N; i++) asm volatile("" : "+r"(r[i])::"memory");
}
__device__ __forceinline__ uint4 ldg128(const void* p) {
  uint4 v; asm volatile("ld.global.L1::no_allocate.v4.u32 {%0,%1,%2,%3}, [%4];" : "=r"(v.x), "=r"(v.y), "=r"(v.z), "=r"(v.w) : "l"(p) : "memory"); return v;
}
__device__ __forceinline__ uint32_t ldg32(const void* p) { uint32_t v; asm volatile("ld.global.u32 %0, [%1];" : "=r"(v) : "l"(p) : "memory"); return v; }
__device__ __forceinline__ uint4 ldg128_nc(const void* p) {
  uint4 v; asm volatile("ld.global.nc.L1::no_allocate.v4.u32 {%0,%1,%2,%3}, [%4];" : "=r"(v.x), "=r"(v.y), "=r"(v.z), "=r"(v.w) : "l"(p)); return v;
}
__device__ __forceinline__ uint32_t pack_bf16(float lo, float hi) { uint32_t r; asm("cvt.rn.bf16x2.f32 %0, %1, %2;" : "=r"(r) : "f"(hi), "f"(lo)); return r; }
__device__ __forceinline__ uint32_t pack_f16(float lo, float hi) { uint32_t r; asm("cvt.rn.satfinite.f16x2.f32 %0, %1, %2;" : "=r"(r) : "f"(hi), "f"(lo)); return r; }
__device__ __forceinline__ float bf_lo(uint32_t v) { return __uint_as_float(v << 16); }
__device__ __forceinline__ float bf_hi(uint32_t v) { return __uint_as_float(v & 0xffff0000u); }
__device__ __forceinline__ uint32_t bf_fma2(uint32_t a, uint32_t b, uint32_t c) { uint32_t r; asm("fma.rn.bf16x2 %0, %1, %2, %3;" : "=r"(r) : "r"(a), "r"(b), "r"(c)); return r; }
__device__ __forceinline__ float ex2f(float x) { float r; asm("ex2.approx.ftz.f32 %0, %1;" : "=f"(r) : "f"(x)); return r; }
__device__ __forceinline__ float rcpf(float x) { float r; asm("rcp.approx.ftz.f32 %0, %1;" : "=f"(r) : "f"(x)); return r; }
__device__ __forceinline__ uint32_t desc_lo(uint32_t addr, uint32_t lbo) { return ((addr & 0x3FFFF) >> 4) | ((lbo >> 4) << 16); }
#define MMA(fn, off, accum, d, a, dlo) fn(d, a, dlo, off, accum)
__device__ __forceinline__ uint64_t desc_plain(uint32_t addr, uint32_t lbo, uint32_t sbo) {
  return (uint64_t)((addr & 0x3FFFF) >> 4) | ((uint64_t)(lbo >> 4) << 16) | ((uint64_t)(sbo >> 4) << 32);
}
#define NPOLY 9
__host__ __device__ constexpr bool poly_grp(int j) { return ((j & 15) * NPOLY) / 16 != (((j & 15) + 1) * NPOLY) / 16; }
#define CRS 1
#define QRS 1
#undef TS
#define TS(k, s, cond)
__device__ __forceinline__ void mma_qk64(uint32_t* d, uint64_t ac, uint64_t bc, uint64_t aq, uint64_t bk, const uint32_t* q, uint32_t c0, uint32_t c1) {
  asm volatile("wgmma.mma_async.sync.aligned.m64n64k16.f16.f16.f16 {%0,%1,%2,%3,%4,%5,%6,%7,%8,%9,%10,%11,%12,%13,%14,%15}, {%18,%19,%20,%20}, %16, 0, 1, 1, 0;\n"
    "wgmma.mma_async.sync.aligned.m64n64k16.f16.f16.f16 {%0,%1,%2,%3,%4,%5,%6,%7,%8,%9,%10,%11,%12,%13,%14,%15}, {%21,%22,%23,%24}, %17, 1, 1, 1, 0;"
    : "=&r"(d[0]),"=&r"(d[1]),"=&r"(d[2]),"=&r"(d[3]),"=&r"(d[4]),"=&r"(d[5]),"=&r"(d[6]),"=&r"(d[7]),"=&r"(d[8]),"=&r"(d[9]),"=&r"(d[10]),"=&r"(d[11]),"=&r"(d[12]),"=&r"(d[13]),"=&r"(d[14]),"=&r"(d[15])
    : "l"(bc), "l"(bk), "r"(c0), "r"(c1), "r"(0), "r"(q[0]), "r"(q[1]), "r"(q[2]), "r"(q[3]));
}
__device__ __forceinline__ void mma_pv(float* d, const uint32_t* a, uint64_t desc) {
  asm volatile("wgmma.mma_async.sync.aligned.m64n24k16.f32.f16.f16 {%0,%1,%2,%3,%4,%5,%6,%7,%8,%9,%10,%11}, {%12,%13,%14,%15}, %16, 1, 1, 1, 1;"
    : "+f"(d[0]),"+f"(d[1]),"+f"(d[2]),"+f"(d[3]),"+f"(d[4]),"+f"(d[5]),"+f"(d[6]),"+f"(d[7]),"+f"(d[8]),"+f"(d[9]),"+f"(d[10]),"+f"(d[11])
    : "r"(a[0]), "r"(a[1]), "r"(a[2]), "r"(a[3]), "l"(desc));
}
__device__ __forceinline__ void mma_n64(float* d, const uint32_t* a, uint32_t dlo, int off, int acc) {
  asm volatile("{.reg .pred p; .reg .b32 t; .reg .b64 ds; add.u32 t, %36, %37; mov.b64 ds, {t, 0x40000040}; setp.ne.b32 p, %38, 0;\n"
    "wgmma.mma_async.sync.aligned.m64n64k16.f32.bf16.bf16 {%0,%1,%2,%3,%4,%5,%6,%7,%8,%9,%10,%11,%12,%13,%14,%15,%16,%17,%18,%19,%20,%21,%22,%23,%24,%25,%26,%27,%28,%29,%30,%31}, "
    "{%32,%33,%34,%35}, ds, p, 1, 1, 1;}"
    : "+f"(d[0]),"+f"(d[1]),"+f"(d[2]),"+f"(d[3]),"+f"(d[4]),"+f"(d[5]),"+f"(d[6]),"+f"(d[7]),"+f"(d[8]),"+f"(d[9]),"+f"(d[10]),"+f"(d[11]),"+f"(d[12]),"+f"(d[13]),"+f"(d[14]),"+f"(d[15]),"+f"(d[16]),"+f"(d[17]),"+f"(d[18]),"+f"(d[19]),"+f"(d[20]),"+f"(d[21]),"+f"(d[22]),"+f"(d[23]),"+f"(d[24]),"+f"(d[25]),"+f"(d[26]),"+f"(d[27]),"+f"(d[28]),"+f"(d[29]),"+f"(d[30]),"+f"(d[31])
    : "r"(a[0]), "r"(a[1]), "r"(a[2]), "r"(a[3]), "r"(dlo), "r"(off >> 4), "r"(acc));
}
__device__ __forceinline__ void mma_n128(float* d, const uint32_t* a, uint32_t dlo, int off, int acc) {
  asm volatile("{.reg .pred p; .reg .b32 t; .reg .b64 ds; add.u32 t, %68, %69; mov.b64 ds, {t, 0x40000040}; setp.ne.b32 p, %70, 0;\n"
    "wgmma.mma_async.sync.aligned.m64n128k16.f32.bf16.bf16 {%0,%1,%2,%3,%4,%5,%6,%7,%8,%9,%10,%11,%12,%13,%14,%15,%16,%17,%18,%19,%20,%21,%22,%23,%24,%25,%26,%27,%28,%29,%30,%31,%32,%33,%34,%35,%36,%37,%38,%39,%40,%41,%42,%43,%44,%45,%46,%47,%48,%49,%50,%51,%52,%53,%54,%55,%56,%57,%58,%59,%60,%61,%62,%63}, "
    "{%64,%65,%66,%67}, ds, p, 1, 1, 1;}"
    : "+f"(d[0]),"+f"(d[1]),"+f"(d[2]),"+f"(d[3]),"+f"(d[4]),"+f"(d[5]),"+f"(d[6]),"+f"(d[7]),"+f"(d[8]),"+f"(d[9]),"+f"(d[10]),"+f"(d[11]),"+f"(d[12]),"+f"(d[13]),"+f"(d[14]),"+f"(d[15]),"+f"(d[16]),"+f"(d[17]),"+f"(d[18]),"+f"(d[19]),"+f"(d[20]),"+f"(d[21]),"+f"(d[22]),"+f"(d[23]),"+f"(d[24]),"+f"(d[25]),"+f"(d[26]),"+f"(d[27]),"+f"(d[28]),"+f"(d[29]),"+f"(d[30]),"+f"(d[31]),"+f"(d[32]),"+f"(d[33]),"+f"(d[34]),"+f"(d[35]),"+f"(d[36]),"+f"(d[37]),"+f"(d[38]),"+f"(d[39]),"+f"(d[40]),"+f"(d[41]),"+f"(d[42]),"+f"(d[43]),"+f"(d[44]),"+f"(d[45]),"+f"(d[46]),"+f"(d[47]),"+f"(d[48]),"+f"(d[49]),"+f"(d[50]),"+f"(d[51]),"+f"(d[52]),"+f"(d[53]),"+f"(d[54]),"+f"(d[55]),"+f"(d[56]),"+f"(d[57]),"+f"(d[58]),"+f"(d[59]),"+f"(d[60]),"+f"(d[61]),"+f"(d[62]),"+f"(d[63])
    : "r"(a[0]), "r"(a[1]), "r"(a[2]), "r"(a[3]), "r"(dlo), "r"(off >> 4), "r"(acc));
}
__device__ __forceinline__ void mma_n48(float* d, const uint32_t* a, uint32_t dlo, int off, int acc) {
  asm volatile("{.reg .pred p; .reg .b32 t; .reg .b64 ds; add.u32 t, %28, %29; mov.b64 ds, {t, 0x40000040}; setp.ne.b32 p, %30, 0;\n"
    "wgmma.mma_async.sync.aligned.m64n48k16.f32.bf16.bf16 {%0,%1,%2,%3,%4,%5,%6,%7,%8,%9,%10,%11,%12,%13,%14,%15,%16,%17,%18,%19,%20,%21,%22,%23}, "
    "{%24,%25,%26,%27}, ds, p, 1, 1, 1;}"
    : "+f"(d[0]),"+f"(d[1]),"+f"(d[2]),"+f"(d[3]),"+f"(d[4]),"+f"(d[5]),"+f"(d[6]),"+f"(d[7]),"+f"(d[8]),"+f"(d[9]),"+f"(d[10]),"+f"(d[11]),"+f"(d[12]),"+f"(d[13]),"+f"(d[14]),"+f"(d[15]),"+f"(d[16]),"+f"(d[17]),"+f"(d[18]),"+f"(d[19]),"+f"(d[20]),"+f"(d[21]),"+f"(d[22]),"+f"(d[23])
    : "r"(a[0]), "r"(a[1]), "r"(a[2]), "r"(a[3]), "r"(dlo), "r"(off >> 4), "r"(acc));
}

__device__ __forceinline__ float silu_bf(bf16 c) {
  const float v = __bfloat162float(c);
  return __bfloat162float(__float2bfloat16(v * rcpf(1.f + ex2f(v * -1.4426950408889634f))));
}
__device__ __forceinline__ void axpy8(float* acc, float s, uint4 v) {
  const uint32_t u[4] = {v.x, v.y, v.z, v.w};
#pragma unroll
  for (int e = 0; e < 4; e++) { acc[2 * e] += s * bf_lo(u[e]); acc[2 * e + 1] += s * bf_hi(u[e]); }
}
__device__ __forceinline__ void store_mod(int col, float s) {
  bf16 m = __float2bfloat16(s);
  if ((col >> 9) == 1 || (col >> 9) == 4) m = __float2bfloat16(1.f + __bfloat162float(m));
  g_mod[col] = m;
}
__global__ void __launch_bounds__(256, 8) k_mod(const bf16* __restrict__ c, const bf16* __restrict__ wm) {
  TS(0, 0, threadIdx.x == 0);
  pdl_trigger();
  __shared__ float red[8][16];
  const int tid = threadIdx.x, r = tid >> 1, lane = tid & 31, w = tid >> 5;
  uint4 v[4];
  bf16 cv[4];
#pragma unroll
  for (int i = 0; i < 4; i++) v[i] = ldg128_nc(wm + (size_t)(r + 128 * i) * (6 * D_) + blockIdx.x * 16 + (tid & 1) * 8);
#pragma unroll
  for (int i = 0; i < 4; i++) cv[i] = c[r + 128 * i];
  if (blockIdx.x < 8) g_flags[blockIdx.x * 256 + tid] = 0;
  float acc[8] = {0.f, 0.f, 0.f, 0.f, 0.f, 0.f, 0.f, 0.f};
#pragma unroll
  for (int i = 0; i < 4; i++) axpy8(acc, silu_bf(cv[i]), v[i]);
#pragma unroll
  for (int e = 0; e < 8; e++) {
#pragma unroll
    for (int m = 2; m < 32; m *= 2) acc[e] += __shfl_xor_sync(~0u, acc[e], m);
    if (lane < 2) red[w][lane * 8 + e] = acc[e];
  }
  __syncthreads();
  if (tid < 16) {
    float s = 0.f;
#pragma unroll
    for (int i = 0; i < 8; i++) s += red[i][tid];
    store_mod(blockIdx.x * 16 + tid, s);
  }
  TS(0, 1, tid == 0);
}

#define EARLY 3
#define WAT 20
__device__ __forceinline__ void hmma(float* d, const uint32_t* a, uint32_t b0, uint32_t b1) {
  asm("mma.sync.aligned.m16n8k16.row.col.f32.bf16.bf16.f32 {%0,%1,%2,%3}, {%4,%5,%6,%7}, {%8,%9}, {%0,%1,%2,%3};"
      : "+f"(d[0]), "+f"(d[1]), "+f"(d[2]), "+f"(d[3]) : "r"(a[0]), "r"(a[1]), "r"(a[2]), "r"(a[3]), "r"(b0), "r"(b1));
}
constexpr int QKV_SMEM = 24 * 8192 + 2048 + 256 + 1024;
__global__ void __launch_bounds__(256, 1) k_qkv(const __grid_constant__ CUtensorMap tm_w, const bf16* __restrict__ x, const bf16* __restrict__ wq) {
  extern __shared__ __align__(1024) uint8_t sp[];
  const uint32_t sb = smem_u32(sp), dlo = desc_lo(sb, 8192);
  const uint32_t bars = sb + 24 * 8192 + 2048;
  const int tid = threadIdx.x, lane = tid & 31, w = tid >> 5, g = lane >> 2, q = lane & 3;
  const int nt = blockIdx.x & 7, rb16 = (blockIdx.x >> 3) * 8 + w;
  TS(1, 0, tid == 0);
  pdl_trigger();
  auto load_w = [&]() {
    for (int kb = 0; kb < 4; kb++)
      tma5d(sb + (w * 4 + kb) * 8192, &tm_w, nt * 192 + (w >> 1) * 64, ((w & 1) * 4 + kb) * 2, bars + 8 * w);
  };
  uint32_t a[128];
  {
    const bf16* x0 = x + (size_t)(rb16 * 16 + g) * D_ + q * 8;
#pragma unroll
    for (int b = 0; b < 16; b++) {
      uint4 u = ldg128(x0 + b * 32), v = ldg128(x0 + 8 * D_ + b * 32);
      a[8 * b] = u.x; a[8 * b + 2] = u.y; a[8 * b + 4] = u.z; a[8 * b + 6] = u.w;
      a[8 * b + 1] = v.x; a[8 * b + 3] = v.y; a[8 * b + 5] = v.z; a[8 * b + 7] = v.w;
    }
    if (lane == 0) {
      if (w < 6) {
        mbar_init(bars + 8 * w, 1);
        mbar_expect(bars + 8 * w, 4 * 8192);
        asm volatile("fence.mbarrier_init.release.cluster;" ::: "memory");
      } else if (w == 6) l2_prefetch((const uint8_t*)wq + blockIdx.x * 12288, 12288);
      else asm volatile("prefetch.tensormap [%0];" ::"l"(&tm_w) : "memory");
    }
    float sm[4] = {0.f, 0.f, 0.f, 0.f}, sq0[4] = {0.f, 0.f, 0.f, 0.f}, sq1[4] = {0.f, 0.f, 0.f, 0.f};
#pragma unroll
    for (int ks = 0; ks < 32; ks++) {
      const uint32_t* f = a + 4 * ks;
      hmma(sm, f, 0x3F803F80u, 0x3F803F80u);
      hmma(sq0, f, f[0], f[2]);
      hmma(sq1, f, f[1], f[3]);
      if (ks == WAT && lane == 0 && w < EARLY) load_w();
    }
    TS(1, 1, tid == 0 && sm[0] != 1.2345e30f);
    const float m0 = sm[0] * (1.f / D_), m1 = sm[2] * (1.f / D_);
    const int dl = (lane & 28) + (g >> 1);
    float v0 = __shfl_sync(~0u, (g & 1) ? sq0[1] : sq0[0], dl), v1 = __shfl_sync(~0u, (g & 1) ? sq1[3] : sq1[2], dl);
    v0 = rsqrtf(fmaxf(v0 * (1.f / D_) - m0 * m0, 0.f) + 1e-5f); v1 = rsqrtf(fmaxf(v1 * (1.f / D_) - m1 * m1, 0.f) + 1e-5f);
    const uint32_t one = 0x3F803F80u, nm0 = pack_bf16(-m0, -m0), nm1 = pack_bf16(-m1, -m1);
    const uint32_t r0 = pack_bf16(v0, v0), r1 = pack_bf16(v1, v1);
#pragma unroll
    for (int i = 0; i < 128; i++) a[i] = bf_fma2(bf_fma2(a[i], one, (i & 1) ? nm1 : nm0), (i & 1) ? r1 : r0, 0x80008000u);
  }
  TS(1, 2, tid == 0 && a[127] != 0x12345);
  pdl_wait();
  TS(1, 3, tid == 0);
  if (tid < 128) *(uint4*)(sp + 24 * 8192 + tid * 16) = ldg128((const uint8_t*)g_mod + tid * 16);
  __syncthreads();
  if (lane == 0 && w >= EARLY && w < 6) load_w();
  TS(1, 4, tid == 0);
  float acc[2][32];
#pragma unroll
  for (int kb = 0; kb < 8; kb++) {
#pragma unroll
    for (int b = 2 * kb; b < 2 * kb + 2; b++) {
      uint4 sa = *(const uint4*)(sp + 24 * 8192 + b * 64 + q * 16), ca = *(const uint4*)(sp + 24 * 8192 + 1024 + b * 64 + q * 16);
      uint32_t su[4] = {sa.x, sa.y, sa.z, sa.w}, cu[4] = {ca.x, ca.y, ca.z, ca.w};
#pragma unroll
      for (int j = 0; j < 8; j++) a[8 * b + j] = bf_fma2(a[8 * b + j], cu[j >> 1], su[j >> 1]);
    }
    if ((kb & 3) == 0) mbar_wait(bars + 8 * (kb >> 2), 0);
    wg_fence();
#pragma unroll
    for (int ks = 0; ks < 4; ks++) MMA(mma_n64, kb * 8192 + ks * 2048, kb | ks, acc[0], a + (kb * 4 + ks) * 4, dlo);
  }
  wg_commit();
#pragma unroll
  for (int p = 0; p < 3; p++) {
    if (p < 2) {
      mbar_wait(bars + 8 * (2 * p + 2), 0);
      mbar_wait(bars + 8 * (2 * p + 3), 0);
      wg_fence();
#pragma unroll
      for (int ks = 0; ks < 32; ks++) MMA(mma_n64, (p + 1) * 65536 + ks * 2048, ks, acc[(p + 1) & 1], a + ks * 4, dlo);
      wg_commit();
      wg_wait<1>();
    } else {
      wg_wait<0>();
    }
    float* d = acc[p & 1];
    reg_fence<32>(d);
    TS(1, 5 + p, tid == 0);
    const int col = nt * 192 + p * 64, sec = col >> 9, h0 = (col & 511) >> 4;
    {
      uint32_t* dst = (uint32_t*)(sec == 0 ? g_q : sec == 1 ? g_k : g_v) + (size_t)(h0 * 2 * S_ + rb16 * 16) * 4 + lane;
      const float sc = sec ? 1.f : 0.25f * 1.4426950408889634f;
      const float k0 = (sec == 1 && poly_grp(2 * rb16)) ? 1.f / 512 : sc, k1 = (sec == 1 && poly_grp(2 * rb16 + 1)) ? 1.f / 512 : sc;
#pragma unroll
      for (int jj = 0; jj < 8; jj++) {
        dst[jj * S_ * 4] = pack_f16(d[4 * jj] * k0, d[4 * jj + 1] * k0);
        dst[jj * S_ * 4 + 32] = pack_f16(d[4 * jj + 2] * k1, d[4 * jj + 3] * k1);
      }
    }
  }
  TS(1, 8, tid == 0);
}

__device__ __forceinline__ uint32_t h_max(uint32_t a, uint32_t b) { uint32_t r; asm("max.f16x2 %0, %1, %2;" : "=r"(r) : "r"(a), "r"(b)); return r; }
__device__ __forceinline__ uint32_t h_add(uint32_t a, uint32_t b) { uint32_t r; asm("add.rn.f16x2 %0, %1, %2;" : "=r"(r) : "r"(a), "r"(b)); return r; }
__device__ __forceinline__ uint32_t h_sub(uint32_t a, uint32_t b) { uint32_t r; asm("sub.rn.f16x2 %0, %1, %2;" : "=r"(r) : "r"(a), "r"(b)); return r; }
__device__ __forceinline__ uint32_t h_mul(uint32_t a, uint32_t b) { uint32_t r; asm("mul.rn.f16x2 %0, %1, %2;" : "=r"(r) : "r"(a), "r"(b)); return r; }
__device__ __forceinline__ uint32_t h_fma(uint32_t a, uint32_t b, uint32_t c) { uint32_t r; asm("fma.rn.f16x2 %0, %1, %2, %3;" : "=r"(r) : "r"(a), "r"(b), "r"(c)); return r; }
__device__ __forceinline__ uint32_t h_fma_relu(uint32_t a, uint32_t b, uint32_t c) { uint32_t r; asm("fma.rn.relu.f16x2 %0, %1, %2, %3;" : "=r"(r) : "r"(a), "r"(b), "r"(c)); return r; }
__device__ __forceinline__ uint32_t h_ex2(uint32_t a) { uint32_t r; asm("ex2.approx.f16x2 %0, %1;" : "=r"(r) : "r"(a)); return r; }
__device__ __forceinline__ float h_lo(uint32_t v) { return __half2float(__ushort_as_half((unsigned short)(v & 0xffff))); }
__device__ __forceinline__ float h_hi(uint32_t v) { return __half2float(__ushort_as_half((unsigned short)(v >> 16))); }

__device__ __forceinline__ uint32_t exp2_fma(uint32_t u) {
  const uint32_t n = h_fma_relu(u, 0x02000200u, 0u);
  const uint32_t f = h_fma(n, 0xF800F800u, u);
  uint32_t p = h_fma(f, 0x630D630Du, 0x47C047C0u);
  p = h_fma(p, f, 0x298C298Cu);
  p = h_fma_relu(p, f, 0x08000800u);
  return p + __funnelshift_l(n, n, 10);
}

#define PRE 1
#define TOP 5
__device__ __forceinline__ bool h_gt(uint32_t a, uint32_t b) {
  uint32_t r; asm("{.reg .pred p, q; setp.gt.f16x2 p|q, %1, %2; or.pred p, p, q; selp.u32 %0, 1, 0, p;}" : "=r"(r) : "r"(a), "r"(b)); return r;
}
__device__ __forceinline__ uint32_t row_max(const uint32_t* mx, uint32_t bias) {
  const uint32_t m0 = h_max(mx[0], h_fma(mx[2], 0x60006000u, bias)), m1 = h_max(mx[1], h_fma(mx[3], 0x60006000u, bias));
  uint32_t M = h_max(__byte_perm(m0, m1, 0x5410), __byte_perm(m0, m1, 0x7632));
  M = h_max(M, __shfl_xor_sync(~0u, M, 1));
  return h_max(M, __shfl_xor_sync(~0u, M, 2));
}
constexpr int NS = 16;
template <int J0> __device__ __forceinline__ bool block_over(const uint32_t* s) {
  uint32_t mx[2], pend[2]; int st[2] = {0, 0};
#pragma unroll
  for (int i = 0; i < NS; i++) {
    const int k = poly_grp(J0 + (i >> 1));
    if (st[k] == 0) { mx[k] = s[i]; st[k] = 1; }
    else if (st[k] == 1) { pend[k] = s[i]; st[k] = 2; }
    else { mx[k] = h_max(h_max(mx[k], pend[k]), s[i]); st[k] = 1; }
  }
  return h_gt(h_max(h_max(mx[0], pend[0]), h_fma(h_max(mx[1], pend[1]), 0x60006000u, 0xCA80CA80u)), 0x4BF04BF0u);
}
template <int J0> __device__ __forceinline__ void block_max(const uint32_t* s, uint32_t* mx) {
  uint32_t pend[4]; int st[4] = {0, 0, 0, 0};
#pragma unroll
  for (int i = 0; i < NS; i++) {
    const int k = (poly_grp(J0 + (i >> 1)) ? 2 : 0) + (i & 1);
    if (st[k] == 0) { mx[k] = s[i]; st[k] = 1; }
    else if (st[k] == 1) { pend[k] = s[i]; st[k] = 2; }
    else { mx[k] = h_max(h_max(mx[k], pend[k]), s[i]); st[k] = 1; }
  }
#pragma unroll
  for (int k = 0; k < 4; k++) if (st[k] == 2) mx[k] = h_max(mx[k], pend[k]);
}
__device__ __forceinline__ void set_offset(uint32_t c, uint32_t crow, bool q0, uint32_t* qf) {
  qf[4] = q0 ? __byte_perm(c, 0x3C00u, 0x5410) : 0u; qf[5] = q0 ? __byte_perm(c, 0x3C00u, 0x5432) : 0u;
}
__device__ __forceinline__ void scores(uint32_t* s, uint64_t ac, uint64_t bc, uint64_t aq, uint64_t bk, const uint32_t* qf) {
  wg_fence();
  mma_qk64(s, ac, bc, aq, bk, qf, qf[4], qf[5]);
  wg_commit();
  wg_wait<0>();
  reg_fence<NS>(s);
}
template <int J0>
__device__ __forceinline__ void attn_step(float* o, uint32_t& c, uint32_t crow, bool q0, uint64_t ac, uint64_t bc, uint64_t aq,
                                          uint64_t dk, uint64_t dv, uint32_t* qf) {
  uint32_t s[NS];
  scores(s, ac, bc + J0 * 8, aq, dk + J0 * 8, qf);
  if (__any_sync(~0u, block_over<J0>(s))) {
    uint32_t mx[4];
    block_max<J0>(s, mx);
    const uint32_t up = h_max(h_sub(h_add(row_max(mx, 0xCA80CA80u), 0x66006600u - TOP * 0x10001u), 0x66006600u), 0u);
    const uint32_t cn = h_sub(c, up), dl = h_sub(cn, c), dp = h_mul(dl, 0x18001800u);
    c = cn;
    set_offset(c, crow, q0, qf);
    const float a0 = ex2f(h_lo(dl)), a1 = ex2f(h_hi(dl));
    const uint32_t d0 = __byte_perm(dl, dl, 0x1010), d1 = __byte_perm(dl, dl, 0x3232);
    const uint32_t p0 = __byte_perm(dp, dp, 0x1010), p1 = __byte_perm(dp, dp, 0x3232);
    o[0] *= a0; o[1] *= a0; o[4] *= a0; o[5] *= a0; o[8] *= a0;
    o[2] *= a1; o[3] *= a1; o[6] *= a1; o[7] *= a1; o[10] *= a1;
#pragma unroll
    for (int i = 0; i < NS; i++) s[i] = h_add(s[i], poly_grp(J0 + (i >> 1)) ? ((i & 1) ? p1 : p0) : ((i & 1) ? d1 : d0));
  }
#pragma unroll
  for (int i = 0; i < NS; i++) s[i] = poly_grp(J0 + (i >> 1)) ? exp2_fma(s[i]) : h_ex2(s[i]);
  wg_fence();
#pragma unroll
  for (int ks = 0; ks < 4; ks++) mma_pv(o, s + ks * 4, dv + (J0 / 2 + ks) * 16);
  wg_commit();
  wg_wait<0>();
  reg_fence<12>(o);
}

constexpr int ATT_THREADS = 1024;
constexpr int A_Q = 5 * 32768, A_C = A_Q + 16384, A_B = A_C + 8192, A_BAR = A_B + 4096, ATT_SMEM = A_BAR + 256 + 1024;
__global__ void __launch_bounds__(ATT_THREADS, 1) k_attn(const bf16* __restrict__ wo, const bf16* __restrict__ w1,
                                                 const bf16* __restrict__ w3, const bf16* __restrict__ w2,
                                                 const bf16* __restrict__ cin, const bf16* __restrict__ wm) {
  extern __shared__ __align__(1024) uint8_t sp[];
  const uint32_t sb = smem_u32(sp);
  const uint32_t bars = sb + A_BAR;
  const int tid = threadIdx.x, lane = tid & 31, w = tid >> 5;
  const int head = blockIdx.x >> 2, quarter = blockIdx.x & 3;
  TS(2, 0, tid == 64);
  if (blockIdx.x >= 128) {
    const int col0 = (blockIdx.x - 126) * D_;
    float acc[8] = {0.f, 0.f, 0.f, 0.f, 0.f, 0.f, 0.f, 0.f};
#pragma unroll 1
    for (int r = tid >> 6; r < D_; r += 64) {
      uint4 v[4];
#pragma unroll
      for (int i = 0; i < 4; i++) v[i] = ldg128_nc(wm + (size_t)(r + 16 * i) * (6 * D_) + col0 + (tid & 63) * 8);
#pragma unroll
      for (int i = 0; i < 4; i++) axpy8(acc, silu_bf(cin[r + 16 * i]), v[i]);
    }
    *(float4*)(sp + tid * 32) = make_float4(acc[0], acc[1], acc[2], acc[3]);
    *(float4*)(sp + tid * 32 + 16) = make_float4(acc[4], acc[5], acc[6], acc[7]);
    __syncthreads();
    pdl_wait();
    if (tid < D_) {
      float s = 0.f;
#pragma unroll
      for (int i = 0; i < 16; i++) s += ((const float*)sp)[i * D_ + tid];
      store_mod(col0 + tid, s);
    }
    return;
  }
  if (lane == 0 && w < 17) {
    mbar_init(bars + 8 * w, 1);
    mbar_expect(bars + 8 * w, w < 2 ? 4096 : 8192);
    asm volatile("fence.mbarrier_init.release.cluster;" ::: "memory");
  }
#pragma unroll
  for (int i = 0; i < 2048 / ATT_THREADS; i++) *(uint4*)(sp + 4 * 32768 + (i * ATT_THREADS + tid) * 16) = make_uint4(0x3C003C00u, 0x3C003C00u, 0x3C003C00u, 0x3C003C00u);
  if (tid < 768) *(uint4*)(sp + A_C + tid * 16) = make_uint4((tid >> 7) != 4 ? 0u : poly_grp(tid >> 3) ? 0x26801800u : 0x00003C00u, 0, 0, 0);
  asm volatile("fence.proxy.async.shared::cta;" ::: "memory");
  __syncthreads();
  pdl_wait();
  TS(2, 1, tid == 0);
  const uint32_t kv_dst = sb + (w & 3) * 32768 + (w >> 2) * 4096;
  const uint4* kv_src = (w & 2 ? g_v : g_k) + (head * 2 + (w & 1)) * S_ + (w >> 2) * 256;
  auto load_kv = [&]() {
    bulk_g2s(kv_dst, kv_src, 2048, bars + 8 * (w < 2 ? 16 : (w >> 2) * 2));
    bulk_g2s(kv_dst + 2048, kv_src + 128, 2048, bars + 8 * (w < 2 ? 16 : (w >> 2) * 2 + 1));
  };
  if (lane == 0 && w < 4) load_kv();
  uint32_t qf[6] = {0, 0, 0, 0, 0, 0};
  {
    const uint32_t* qp = (const uint32_t*)(g_q + head * 2 * S_ + quarter * 512 + w * 16) + lane;
    qf[0] = ldg32(qp); qf[1] = ldg32(qp + 32); qf[2] = ldg32(qp + S_ * 4); qf[3] = ldg32(qp + S_ * 4 + 32);
  }
  pdl_trigger();
  const int wg = __shfl_sync(~0u, w >> 2, 0);
  const uint64_t dk0 = desc_plain(sb, 32768, 128), dv0 = desc_plain(sb + 65536, 128, 32768);
  const uint64_t aq = desc_plain(sb + A_Q + wg * 1024, 8192, 128), ac = desc_plain(sb + A_C + wg * 1024, 0, 128);
  const uint64_t bc = desc_plain(sb + A_B, 2048, 128);
  const bool q0 = (lane & 3) == 0;
  const uint32_t crow = sb + A_C + w * 256 + (lane >> 2) * 16;
  float o[12];
#pragma unroll
  for (int i = 0; i < 12; i++) o[i] = 0.f;
  uint32_t c = 0xFBFFFBFFu;
  mbar_wait(bars + 128, 0);
  if (lane == 0 && w >= 4) load_kv();
#pragma unroll 1
  for (int j = 0; j < PRE; j++) {
    uint32_t s[NS], mx[4];
    scores(s, ac, bc, aq, dk0 + j * 128, qf);
    block_max<0>(s, mx);
    c = h_max(c, row_max(mx, 0u));
  }
  TS(2, 2, tid == 0);
  if (lane == 0 && (w & 7) == 5)
    l2_prefetch((const uint8_t*)(w < 8 ? wo : w < 16 ? w1 : w < 24 ? w3 : w2) + blockIdx.x * (w < 8 ? 4096 : 11008), w < 8 ? 4096 : 11008);
  c = h_sub(h_sub(0x66006600u + TOP * 0x10001u, c), 0x66006600u);
  set_offset(c, crow, q0, qf);
#pragma unroll 1
  for (uint32_t kb = 0; kb < S_; kb += 128) {
    mbar_wait(bars + (kb >> 4), 0);
    attn_step<0>(o, c, crow, q0, ac, bc, aq, dk0 + kb, dv0 + kb, qf);
    attn_step<8>(o, c, crow, q0, ac, bc, aq, dk0 + kb, dv0 + kb, qf);
  }
  TS(2, 3, tid == 0);
  TS(2, 5, tid == 896);
  const float i0 = 1.f / o[8], i1 = 1.f / o[10];
  g_attn[((quarter * 32 + w) * 32 + head) * 32 + lane] = make_uint4(pack_bf16(o[0] * i0, o[1] * i0), pack_bf16(o[2] * i1, o[3] * i1),
                                                                    pack_bf16(o[4] * i0, o[5] * i0), pack_bf16(o[6] * i1, o[7] * i1));
}

__device__ float4 g_stats[128 * 8 * 8];
#define WIN 8
#define LDA(i, ptr) { const uint4 u_ = ldg128(ptr); a[4 * (i)] = u_.x; a[4 * (i) + 1] = u_.y; a[4 * (i) + 2] = u_.z; a[4 * (i) + 3] = u_.w; }
#define LA 2
#define RK 6
#define FA 0
#define SK 4
#define MK 5
#define RW 0
#define SP 1
#define NPRE 4
#define PK 3
#define XK -1
constexpr int NST = 13, STB = 16384;
constexpr int FFN_SMEM = NST * STB + 4096 + 512 + 1024;

__device__ __forceinline__ void flag_signal(unsigned* f, int lane) {
  __syncwarp();
  if (lane == 0) asm volatile("red.release.gpu.global.add.u32 [%0], 1;" ::"l"(f) : "memory");
}
__device__ __forceinline__ void flag_wait(const unsigned* f, int lane, unsigned cnt) {
  if (lane == 0) {
    unsigned v, n = 0;
    do {
      asm volatile("ld.acquire.gpu.global.u32 %0, [%1];" : "=r"(v) : "l"(f) : "memory");
      if (++n > (1u << 24)) break;
    } while (v < cnt);
  }
  __syncwarp();
}
__device__ __forceinline__ void quad_xpose(uint32_t& m0, uint32_t& m1, uint32_t& m2, uint32_t& m3, int q) {
  uint32_t t0 = __shfl_xor_sync(~0u, q & 1 ? m0 : m1, 1), t1 = __shfl_xor_sync(~0u, q & 1 ? m2 : m3, 1);
  if (q & 1) { m0 = t0; m2 = t1; } else { m1 = t0; m3 = t1; }
  t0 = __shfl_xor_sync(~0u, q & 2 ? m0 : m2, 2); t1 = __shfl_xor_sync(~0u, q & 2 ? m1 : m3, 2);
  if (q & 2) { m0 = t0; m1 = t1; } else { m2 = t0; m3 = t1; }
}
__device__ __forceinline__ float silu_mul(float g, float u) { return g * u * rcpf(1.f + ex2f(g * -1.4426950408889634f)); }

__global__ void __launch_bounds__(384, 1) __cluster_dims__(2, 1, 1)
k_ffn(const __grid_constant__ CUtensorMap tm_wo, const __grid_constant__ CUtensorMap tm_w1, const __grid_constant__ CUtensorMap tm_w3,
      const __grid_constant__ CUtensorMap tm_w2, const __grid_constant__ CUtensorMap tm_w2b,
      const bf16* __restrict__ x, bf16* __restrict__ out) {
  extern __shared__ __align__(1024) uint8_t sp[];
  const uint32_t sb = smem_u32(sp), dlo = desc_lo(sb, 8192);
  const uint32_t bfull = sb + NST * STB + 4096, bempty = bfull + 8 * NST, bpeer = bempty + 8 * NST, bsig = bpeer + 8, bx = bsig + 16, bgo = bx + 64;
  const int tid = threadIdx.x, lane = tid & 31, w = tid >> 5;
  const int j = blockIdx.x & 7, rb = blockIdx.x >> 3, kh = j & 1;
  TS(3, 0, tid == 64);
  auto init_bars = [&]() {
  if (lane == 0) {
    for (int i = w; i < 2 * NST + 11; i += 12) {
      mbar_init(bfull + 8 * i, i < NST || i > 2 * NST + 2 ? 1 : i > 2 * NST ? 4 : 8);
      if (i > 2 * NST + 2) mbar_expect(bfull + 8 * i, 4096);
    }
    if (w == 11) mbar_init(bgo, 8);
    asm volatile("fence.mbarrier_init.release.cluster;" ::: "memory");
  }
  __syncwarp();
  asm volatile("barrier.cluster.arrive.relaxed.aligned;" ::: "memory");
  };
  if (w >= 8) {
    asm volatile("setmaxnreg.dec.sync.aligned.u32 24;");
    init_bars();
    asm volatile("bar.sync 3, 384;" ::: "memory");
    asm volatile("bar.arrive 4, 384;" ::: "memory");
    if (tid == 256) {
      int slot = 0, ph = 1, lslot = 0, lph = 0;
#pragma unroll 1
      for (int st = 0; st < 36; st++) {
        const CUtensorMap *m0, *m1; int x0, y0, x1, y1;
        if (st < 4) { m0 = m1 = &tm_wo; x0 = x1 = j * 64; y0 = st * 128; y1 = y0 + 64; }
        else if (st < 28) { m0 = &tm_w1; m1 = &tm_w3; x0 = x1 = j * 176 + ((st - 4) >> 3) * 64; y0 = y1 = ((st - 4) & 7) * 64; }
        else { m0 = m1 = &tm_w2; x0 = (j >> 1) * 128; x1 = x0 + 64; y0 = y1 = (kh * 4 + ((st - 28) >> 1)) * 176 + (st & 1) * 64; }
        if (st == NPRE) mbar_wait(bgo, 0);
        if (st >= WIN) {
          mbar_wait(bfull + 8 * lslot, lph);
          if (++lslot == NST) { lslot = 0; lph ^= 1; }
        }
        mbar_wait(bempty + 8 * slot, ph);
        mbar_expect(bfull + 8 * slot, STB);
        tma2d(sb + slot * STB, m0, x0, y0, bfull + 8 * slot);
        tma2d(sb + slot * STB + 8192, m1, x1, y1, bfull + 8 * slot);
        if (++slot == NST) { slot = 0; ph ^= 1; }
      }
      for (int i = 10; i < 13; i++) mbar_wait(bempty + 8 * i, 1);
      mbar_expect(bfull + 80, 3 * STB);
#pragma unroll 1
      for (int i = 0; i < 8; i++)
        tma2d(sb + 10 * STB + i * 6144, &tm_w2b, (j >> 1) * 128 + (i & 1) * 64, (kh * 4 + (i >> 1)) * 176 + 128, bfull + 80);
    } else if (lane == 0 && w < 11 && w > 8) {
#pragma unroll 1
      for (int i = 0; i < 2; i++) {
        mbar_wait(bsig + 8 * (w - 9), i);
        asm volatile("fence.acq_rel.gpu;" ::: "memory");
        asm volatile("red.relaxed.gpu.global.add.u32 [%0], 1;" ::"l"(g_flags + 1024 + i * 512 + (rb * 4 + (w - 9) * 2 + (j >> 2)) * 8) : "memory");
      }
    }
    __syncwarp();
    asm volatile("barrier.cluster.wait.acquire.aligned;" ::: "memory");
  } else {
    asm volatile("setmaxnreg.inc.sync.aligned.u32 240;");
    const int g = lane >> 2, q = lane & 3, rb16 = rb * 8 + w;
    const uint32_t* smod = (const uint32_t*)(sp + NST * STB);
    uint32_t a[128];
    float acc[64];
    uint32_t xr[16];
    uint4 xv[4];
    const uint4* xp = (const uint4*)(x + (size_t)(rb16 * 16 + g) * D_ + j * 64) + q;
    if (XK < 0) { xv[0] = ldg128(xp); xv[1] = ldg128(xp + D_); xv[2] = ldg128(xp + 4); xv[3] = ldg128(xp + D_ + 4); }
    init_bars();
    asm volatile("bar.arrive 3, 384;" ::: "memory");
    TS(3, 1, tid == 0);
    pdl_wait();
    TS(3, 2, tid == 0);
    const uint4 modv = ldg128((const uint8_t*)g_mod + 2048 + tid * 16);
#pragma unroll
    for (int i = 0; i < 4 * LA; i++) LDA(i, g_attn + (rb16 * 32 + i) * 32 + lane);
#pragma unroll
    for (int kb = 0; kb < 8; kb++) {
#pragma unroll
      for (int i = 4 * (kb + LA); i < 4 * (kb + LA + 1) && i < 32; i++) LDA(i, g_attn + (rb16 * 32 + i) * 32 + lane);
      if (kb == XK) { xv[0] = ldg128(xp); xv[1] = ldg128(xp + D_); xv[2] = ldg128(xp + 4); xv[3] = ldg128(xp + D_ + 4); }
      if (kb == 0) asm volatile("bar.sync 4, 384;" ::: "memory");
      if (kb == PK && lane == 0) mbar_arrive(bgo);
      if ((kb & 1) == 0) mbar_wait(bfull + 4 * kb, 0);
      wg_fence();
#pragma unroll
      for (int ks = 0; ks < 4; ks++) MMA(mma_n64, kb * 8192 + ks * 2048, kb | ks, acc, a + (kb * 4 + ks) * 4, dlo);
      if (kb == MK) {
        *(uint4*)(sp + NST * STB + tid * 16) = modv;
        asm volatile("bar.sync 1, 256;" ::: "memory");
      }
    }
    wg_commit();
#pragma unroll
    for (int i = 0; i < 4; i++) {
      const int o = (i >> 1) * 8 + (i & 1);
      xr[o] = xv[i].x; xr[o + 2] = xv[i].y; xr[o + 4] = xv[i].z; xr[o + 6] = xv[i].w;
      quad_xpose(xr[o], xr[o + 2], xr[o + 4], xr[o + 6], q);
    }
    wg_wait<0>();
    reg_fence<32>(acc);
    TS(3, 3, tid == 0);
    {
      float s0 = 0.f, s1 = 0.f;
#pragma unroll
      for (int i = 0; i < 8; i++) {
        const uint32_t ga = smod[j * 32 + i * 4 + q];
        xr[2 * i] = pack_bf16(bf_lo(xr[2 * i]) + bf_lo(ga) * acc[4 * i], bf_hi(xr[2 * i]) + bf_hi(ga) * acc[4 * i + 1]);
        xr[2 * i + 1] = pack_bf16(bf_lo(xr[2 * i + 1]) + bf_lo(ga) * acc[4 * i + 2], bf_hi(xr[2 * i + 1]) + bf_hi(ga) * acc[4 * i + 3]);
        s0 += bf_lo(xr[2 * i]) + bf_hi(xr[2 * i]); s1 += bf_lo(xr[2 * i + 1]) + bf_hi(xr[2 * i + 1]);
      }
#pragma unroll
      for (int i = 0; i < 4; i++) g_x1[(rb16 * 32 + j * 4 + i) * 32 + lane] = make_uint4(xr[4 * i], xr[4 * i + 1], xr[4 * i + 2], xr[4 * i + 3]);
      s0 += __shfl_xor_sync(~0u, s0, 1); s1 += __shfl_xor_sync(~0u, s1, 1);
      s0 += __shfl_xor_sync(~0u, s0, 2); s1 += __shfl_xor_sync(~0u, s1, 2);
      s0 *= 1.f / 64; s1 *= 1.f / 64;
      float v0 = 0.f, v1 = 0.f;
#pragma unroll
      for (int i = 0; i < 8; i++) {
        float d = bf_lo(xr[2 * i]) - s0; v0 += d * d; d = bf_hi(xr[2 * i]) - s0; v0 += d * d;
        d = bf_lo(xr[2 * i + 1]) - s1; v1 += d * d; d = bf_hi(xr[2 * i + 1]) - s1; v1 += d * d;
      }
      v0 += __shfl_xor_sync(~0u, v0, 1); v1 += __shfl_xor_sync(~0u, v1, 1);
      v0 += __shfl_xor_sync(~0u, v0, 2); v1 += __shfl_xor_sync(~0u, v1, 2);
      if (q == 0) g_stats[(rb16 * 8 + j) * 8 + g] = make_float4(s0, v0, s1, v1);
    }
    flag_signal(g_flags + rb16 * 8, lane);
    __syncwarp();
    if (lane < 4) mbar_arrive(bempty + 8 * lane);
    TS(3, 4, tid == 0);
    asm volatile("barrier.cluster.wait.acquire.aligned;" ::: "memory");
    flag_wait(g_flags + rb16 * 8, lane, 8);
    TS(3, 5, tid == 0);
    uint32_t r0, r1, n0, n1;
    {
      const uint4 ta = ldg128(g_stats + (rb16 * 8 + q) * 8 + g), tb = ldg128(g_stats + (rb16 * 8 + q + 4) * 8 + g);
      const uint4 t0 = make_uint4(ta.x, ta.y, tb.x, tb.y), t1 = make_uint4(ta.z, ta.w, tb.z, tb.w);
#pragma unroll
      for (int i = 0; i < 4 * LA; i++) LDA(i, g_x1 + (rb16 * 32 + i) * 32 + lane);
      float m0 = __uint_as_float(t0.x) + __uint_as_float(t0.z), m1 = __uint_as_float(t1.x) + __uint_as_float(t1.z);
      m0 += __shfl_xor_sync(~0u, m0, 1); m1 += __shfl_xor_sync(~0u, m1, 1);
      m0 += __shfl_xor_sync(~0u, m0, 2); m1 += __shfl_xor_sync(~0u, m1, 2);
      m0 *= 0.125f; m1 *= 0.125f;
      float d0 = __uint_as_float(t0.x) - m0, d1 = __uint_as_float(t0.z) - m0;
      float v0 = __uint_as_float(t0.y) + __uint_as_float(t0.w) + 64.f * (d0 * d0 + d1 * d1);
      d0 = __uint_as_float(t1.x) - m1; d1 = __uint_as_float(t1.z) - m1;
      float v1 = __uint_as_float(t1.y) + __uint_as_float(t1.w) + 64.f * (d0 * d0 + d1 * d1);
      v0 += __shfl_xor_sync(~0u, v0, 1); v1 += __shfl_xor_sync(~0u, v1, 1);
      v0 += __shfl_xor_sync(~0u, v0, 2); v1 += __shfl_xor_sync(~0u, v1, 2);
      v0 = rsqrtf(v0 * (1.f / D_) + 1e-5f); v1 = rsqrtf(v1 * (1.f / D_) + 1e-5f);
      r0 = pack_bf16(v0, v0); r1 = pack_bf16(v1, v1);
      m0 *= -bf_lo(r0); m1 *= -bf_lo(r1);
      n0 = pack_bf16(m0, m0); n1 = pack_bf16(m1, m1);
    }
    const unsigned* fl = g_flags + 1024 + (rb * 4 + (w >> 2) * 2 + kh) * 8;
    const uint4* ap = g_act + (rb16 * KS_F + kh * 44) * 32 + lane;
#pragma unroll
    for (int p = 0; p < 3; p++) {
      float g48[24], u48[24];
#pragma unroll
      for (int kb = 0; kb < 8; kb++) {
        const int st = 4 + p * 8 + kb, slot = st % NST;
        if (p == 0) {
#pragma unroll
          for (int i = 4 * (kb + LA); i < 4 * (kb + LA + 1) && i < 32; i++) LDA(i, g_x1 + (rb16 * 32 + i) * 32 + lane);
#pragma unroll
          for (int i = kb * 8; i < kb * 8 + 8; i++) {
            const uint32_t sv = smod[256 + i * 4 + q], cv = smod[512 + i * 4 + q];
            a[2 * i] = bf_fma2(bf_fma2(a[2 * i], r0, n0), cv, sv);
            a[2 * i + 1] = bf_fma2(bf_fma2(a[2 * i + 1], r1, n1), cv, sv);
          }
        }
        if (p == SP && kb == 0 && w >= 4) asm volatile("bar.sync 2, 256;" ::: "memory");
        if (p == SP && kb == SK && w < 4) asm volatile("bar.arrive 2, 256;" ::: "memory");
        mbar_wait(bfull + 8 * slot, (st / NST) & 1);
        wg_fence();
#pragma unroll
        for (int ks = 0; ks < 4; ks++) {
          if (p < 2) MMA(mma_n128, slot * STB + ks * 2048, kb | ks, acc, a + (kb * 4 + ks) * 4, dlo);
          else {
            MMA(mma_n48, slot * STB + ks * 2048, kb | ks, g48, a + (kb * 4 + ks) * 4, dlo);
            MMA(mma_n48, slot * STB + 8192 + ks * 2048, kb | ks, u48, a + (kb * 4 + ks) * 4, dlo);
          }
        }
        wg_commit();
        if (kb > 0) { wg_wait<1>(); if (lane == 0) mbar_arrive(bempty + 8 * ((st - 1) % NST)); }
      }
      if (p == 2 && !FA) flag_wait(fl, lane, 4);
      wg_wait<0>();
      if (p < 2) reg_fence<64>(acc); else { reg_fence<24>(g48); reg_fence<24>(u48); }
      TS(3, 6 + p, tid == 0);
      if (lane == 0) {
        mbar_arrive(bempty + 8 * ((4 + p * 8 + 7) % NST));
        if (p == 2) {
          uint32_t ra; asm volatile("mapa.shared::cluster.u32 %0, %1, %2;" : "=r"(ra) : "r"(bpeer), "r"(kh ^ 1));
          asm volatile("mbarrier.arrive.shared::cluster.b64 _, [%0];" ::"r"(ra) : "memory");
        }
      }
      if (p == 2 && !FA) {
#pragma unroll
        for (int i = 0; i < 4 * LA; i++) LDA(i, ap + ((i >> 3) * 11 + (i & 7)) * 32);
      }
#pragma unroll
      for (int ks = 0; ks < (p < 2 ? 4 : 3); ks++) {
        const int kk = j * 11 + p * 4 + ks;
        const float* gt = (p < 2 ? acc : g48) + 8 * ks; const float* up = (p < 2 ? acc + 32 : u48) + 8 * ks;
        uint4 u = make_uint4(pack_bf16(silu_mul(gt[0], up[0]), silu_mul(gt[1], up[1])), pack_bf16(silu_mul(gt[2], up[2]), silu_mul(gt[3], up[3])),
                             pack_bf16(silu_mul(gt[4], up[4]), silu_mul(gt[5], up[5])), pack_bf16(silu_mul(gt[6], up[6]), silu_mul(gt[7], up[7])));
        if (kk < KS_F) g_act[(rb16 * KS_F + kk) * 32 + lane] = u;
      }
      if (p > 0) { __syncwarp(); if (lane == 0) mbar_arrive(bsig + 8 * (w >> 2)); }
    }
    TS(3, 10, tid == 0);
    if (FA) {
      flag_wait(fl, lane, 4);
#pragma unroll
      for (int i = 0; i < 4 * LA; i++) LDA(i, ap + ((i >> 3) * 11 + (i & 7)) * 32);
    }
    float acc3[64];
#pragma unroll
    for (int kb = 0; kb < 8; kb++) {
#pragma unroll
      for (int i = 4 * (kb + LA); i < 4 * (kb + LA + 1) && i < 32; i++) LDA(i, ap + ((i >> 3) * 11 + (i & 7)) * 32);
      mbar_wait(bfull + 8 * (2 + kb), 0);
      wg_fence();
#pragma unroll
      for (int ks = 0; ks < 4; ks++) MMA(mma_n128, (2 + kb) * STB + ks * 2048, kb | ks, acc3, a + (kb * 4 + ks) * 4, dlo);
      wg_commit();
      if (kb == RK) {
        flag_wait(fl + 512, lane, 4);
        wg_wait<RW>();
        if (RW == 0) reg_fence<64>(acc3);
        TS(3, 11, tid == 0);
#pragma unroll
        for (int i = 0; i < 12; i++) {
          uint4 u = make_uint4(0, 0, 0, 0);
          if (i < 10 || kh == 0) u = ldg128(ap + ((i / 3) * 11 + 8 + i % 3) * 32);
          a[4 * i] = u.x; a[4 * i + 1] = u.y; a[4 * i + 2] = u.z; a[4 * i + 3] = u.w;
        }
      }
    }
    mbar_wait(bfull + 80, 0);
    wg_fence();
#pragma unroll
    for (int i = 0; i < 12; i++) MMA(mma_n128, 10 * STB + (i / 3) * 12288 + (i % 3) * 2048, 1, acc3, a + i * 4, desc_lo(sb, 6144));
    wg_commit();
#pragma unroll
    for (int i = 0; i < 4; i++) { uint4 u = ldg128(g_x1 + (rb16 * 32 + j * 4 + i) * 32 + lane); xr[4 * i] = u.x; xr[4 * i + 1] = u.y; xr[4 * i + 2] = u.z; xr[4 * i + 3] = u.w; }
    mbar_wait_cluster(bpeer, 0);
    wg_wait<0>();
    reg_fence<64>(acc3);
    TS(3, 12, tid == 0);
    {
      uint32_t ra, rbar;
      asm volatile("mapa.shared::cluster.u32 %0, %1, %2;" : "=r"(ra) : "r"(sb + tid * 16), "r"(kh ^ 1));
      asm volatile("mapa.shared::cluster.u32 %0, %1, %2;" : "=r"(rbar) : "r"(bx + 8 * w), "r"(kh ^ 1));
#pragma unroll
      for (int i = 0; i < 8; i++) {
        const float s0 = kh ? acc3[4 * i] : acc3[32 + 4 * i], s1 = kh ? acc3[4 * i + 1] : acc3[33 + 4 * i];
        const float s2 = kh ? acc3[4 * i + 2] : acc3[34 + 4 * i], s3 = kh ? acc3[4 * i + 3] : acc3[35 + 4 * i];
        asm volatile("st.async.weak.shared::cluster.mbarrier::complete_tx::bytes.v4.f32 [%0], {%1,%2,%3,%4}, [%5];"
                     ::"r"(ra + i * 4096), "f"(s0), "f"(s1), "f"(s2), "f"(s3), "r"(rbar) : "memory");
      }
    }
    mbar_wait_cluster(bx + 8 * w, 0);
    TS(3, 13, tid == 0);
    uint32_t* o0 = (uint32_t*)(out + (size_t)(rb16 * 16 + g) * D_ + j * 64) + q;
#pragma unroll
    for (int i = 0; i < 8; i++) {
      const float4 pv = *(const float4*)(sp + i * 4096 + tid * 16);
      const uint32_t gb = smod[768 + j * 32 + i * 4 + q];
      const float s0 = (kh ? acc3[32 + 4 * i] : acc3[4 * i]) + pv.x, s1 = (kh ? acc3[33 + 4 * i] : acc3[4 * i + 1]) + pv.y;
      const float s2 = (kh ? acc3[34 + 4 * i] : acc3[4 * i + 2]) + pv.z, s3 = (kh ? acc3[35 + 4 * i] : acc3[4 * i + 3]) + pv.w;
      xr[2 * i] = pack_bf16(bf_lo(xr[2 * i]) + bf_lo(gb) * s0, bf_hi(xr[2 * i]) + bf_hi(gb) * s1);
      xr[2 * i + 1] = pack_bf16(bf_lo(xr[2 * i + 1]) + bf_lo(gb) * s2, bf_hi(xr[2 * i + 1]) + bf_hi(gb) * s3);
      if ((i & 3) == 3) {
        uint4* o4 = (uint4*)(o0 - q) + q + (i >> 2) * 4;
        const int o = 2 * i - 6;
        quad_xpose(xr[o], xr[o + 2], xr[o + 4], xr[o + 6], q);
        quad_xpose(xr[o + 1], xr[o + 3], xr[o + 5], xr[o + 7], q);
        o4[0] = make_uint4(xr[o], xr[o + 2], xr[o + 4], xr[o + 6]);
        o4[D_] = make_uint4(xr[o + 1], xr[o + 3], xr[o + 5], xr[o + 7]);
      }
    }
    TS(3, 14, tid == 0);
  }
}

typedef CUresult (*EncodeFn)(CUtensorMap*, CUtensorMapDataType, cuuint32_t, void*, const cuuint64_t*, const cuuint64_t*,
                             const cuuint32_t*, const cuuint32_t*, CUtensorMapInterleave, CUtensorMapSwizzle,
                             CUtensorMapL2promotion, CUtensorMapFloatOOBfill);
static void make_map(EncodeFn enc, CUtensorMap* m, const void* p, int rank, const cuuint64_t* dims, const cuuint64_t* strides, const cuuint32_t* box) {
  const cuuint32_t es[5] = {1, 1, 1, 1, 1};
  enc(m, CU_TENSOR_MAP_DATA_TYPE_BFLOAT16, rank, (void*)p, dims, strides, box, es, CU_TENSOR_MAP_INTERLEAVE_NONE,
      CU_TENSOR_MAP_SWIZZLE_128B, CU_TENSOR_MAP_L2_PROMOTION_L2_256B, CU_TENSOR_MAP_FLOAT_OOB_FILL_NONE);
}
static void make_map2(EncodeFn enc, CUtensorMap* m, const void* p, int cols, int rows, int brows = 64) {
  const cuuint64_t dims[2] = {(cuuint64_t)cols, (cuuint64_t)rows}, st[1] = {(cuuint64_t)cols * 2};
  const cuuint32_t box[2] = {64, (cuuint32_t)brows};
  make_map(enc, m, p, 2, dims, st, box);
}
template <typename... KA, typename... A>
static void launch(void (*k)(KA...), int grid, int block, int smem, bool pdl, A... args) {
  cudaLaunchConfig_t cfg = {};
  cfg.gridDim = dim3(grid); cfg.blockDim = dim3(block); cfg.dynamicSmemBytes = smem; cfg.stream = cudaStreamPerThread;
  cudaLaunchAttribute at[1];
  at[0].id = cudaLaunchAttributeProgrammaticStreamSerialization;
  at[0].val.programmaticStreamSerializationAllowed = 1;
  cfg.attrs = at; cfg.numAttrs = pdl ? 1 : 0;
  cudaLaunchKernelEx(&cfg, k, KA(args)...);
}

extern "C" void kernel_launch(void* const* d_in, const int* in_sizes, int n_in, void* d_out, int out_size) {
  const bf16 *x = (const bf16*)d_in[0], *wqkv = (const bf16*)d_in[1], *wo = (const bf16*)d_in[2];
  const bf16 *w1 = (const bf16*)d_in[4], *w3 = (const bf16*)d_in[5], *w2 = (const bf16*)d_in[6];
  const bf16 *c = (const bf16*)d_in[7], *wm = (const bf16*)d_in[8];
  void* fn = nullptr;
  cudaDriverEntryPointQueryResult qr;
  cudaGetDriverEntryPoint("cuTensorMapEncodeTiled", &fn, cudaEnableDefault, &qr);
  EncodeFn enc = (EncodeFn)fn;
  CUtensorMap m_qkv, m_o, m_1, m_3, m_2, m_2b;
  {
    const cuuint64_t rs = 3 * D_ * 2, dims[5] = {3 * D_, 2, 4, 4, 16}, st[4] = {rs, 8 * rs, 2 * rs, 32 * rs};
    const cuuint32_t box[5] = {64, 2, 4, 4, 2};
    make_map(enc, &m_qkv, wqkv, 5, dims, st, box);
  }
  make_map2(enc, &m_o, wo, D_, D_);
  make_map2(enc, &m_1, w1, F_, D_);
  make_map2(enc, &m_3, w3, F_, D_);
  make_map2(enc, &m_2, w2, D_, F_);
  make_map2(enc, &m_2b, w2, D_, F_, 48);
  cudaFuncSetAttribute(k_qkv, cudaFuncAttributeMaxDynamicSharedMemorySize, QKV_SMEM);
  cudaFuncSetAttribute(k_attn, cudaFuncAttributeMaxDynamicSharedMemorySize, ATT_SMEM);
  cudaFuncSetAttribute(k_ffn, cudaFuncAttributeMaxDynamicSharedMemorySize, FFN_SMEM);
  cudaFuncSetAttribute(k_mod, cudaFuncAttributePreferredSharedMemoryCarveout, 100);
  launch(k_mod, 64, 256, 0, false, c, wm);
  launch(k_qkv, 128, 256, QKV_SMEM, true, m_qkv, x, wqkv);
  launch(k_attn, 132, ATT_THREADS, ATT_SMEM, true, wo, w1, w3, w2, c, wm);
  launch(k_ffn, 128, 384, FFN_SMEM, true, m_o, m_1, m_3, m_2, m_2b, x, (bf16*)d_out);
}
```
